```python
import torch

def _softmax(x, axis=-1):
    return torch.softmax(x, dim=axis)
def _gelu(x):
    return torch.nn.functional.gelu(x, approximate="tanh")
def _silu(x):
    return torch.nn.functional.silu(x)
def _sigmoid(x):
    return torch.sigmoid(x)
def _layernorm(x, axis=-1, eps=1e-5):
    m = x.mean(dim=axis, keepdim=True)
    v = x.var(dim=axis, keepdim=True, unbiased=False)
    return (x - m) / torch.sqrt(v + eps)
def _scatter_add(tgt, idx, src, axis=0):
    return tgt.clone().index_add_(axis, idx, src)
def _segment_sum(src, seg, n):
    out = torch.zeros((n,) + src.shape[1:], dtype=src.dtype)
    return out.index_add_(0, seg, src)
def _pad(x, pw):
    flat = tuple(v for pair in reversed(pw) for v in pair)
    return torch.nn.functional.pad(x, flat)

kernel_name = 'sequential_preLN__mha_block_cached__dense_activation_squared_relu__decode'

def setup_inputs():

    _w = (lambda a: (lambda t: t.to(torch.bfloat16) if t.is_floating_point() else t)(torch.as_tensor(a)))
    def _A_setup():
        B, Sq, D = 8, 1, 448
        H, Sk, Dh = 16, 4096, 256
        return {
            "x": _w((lambda *s: torch.randn(*s, dtype=torch.bfloat16) * 0.05)(B, Sq, D)),
            "k_cache": _w((lambda *s: torch.randn(*s, dtype=torch.bfloat16) * 3.2)(B, H, Sk, Dh)),
            "v_cache": _w((lambda *s: torch.randn(*s, dtype=torch.bfloat16) * 0.4)(B, H, Sk, Dh)),
            "wq": _w((lambda *s: torch.randn(*s, dtype=torch.bfloat16) * 3.2)(D, H * Dh) * (D ** -0.5)),
            "wo": _w((lambda *s: torch.randn(*s, dtype=torch.bfloat16) * 0.4)(H * Dh, D) * ((H * Dh) ** -0.5)),
        }
    _A_in = _A_setup()

    def _B_setup():
        B, S, D, F = 8, 1, 448, 1792
        return {
            "x": _w((lambda *s: torch.randn(*s, dtype=torch.bfloat16) * 0.05)(B, S, D)),
            "w1": _w((lambda *s: torch.randn(*s, dtype=torch.bfloat16) * 0.05)(D, F)),
            "b1": _w((lambda *s: torch.randn(*s, dtype=torch.bfloat16) * 0.8)(F)),
            "w2": _w((lambda *s: torch.randn(*s, dtype=torch.bfloat16) * 0.05)(F, D)),
            "b2": _w((lambda *s: torch.randn(*s, dtype=torch.bfloat16) * 3.2)(D)),
        }
    _B_in = _B_setup()

    return {
        "A_x": _A_in["x"],
        "A_k_cache": _A_in["k_cache"],
        "A_v_cache": _A_in["v_cache"],
        "A_wq": _A_in["wq"],
        "A_wo": _A_in["wo"],
        "B_x": _B_in["x"],
        "B_w1": _B_in["w1"],
        "B_b1": _B_in["b1"],
        "B_w2": _B_in["w2"],
        "B_b2": _B_in["b2"],
    }

def reference(A_x, A_k_cache, A_v_cache, A_wq, A_wo, B_x, B_w1, B_b1, B_w2, B_b2):
    def _A_ref(x, k_cache, v_cache, wq, wo):
        B, Sq, D = x.shape
        H, Dh = 16, 256
        q = (lambda x, *d: x.permute(*d))((x @ wq).reshape(B, Sq, H, Dh), 0, 2, 1, 3)
        scores = torch.einsum("bhqd,bhkd->bhqk", q, k_cache) * (Dh ** -0.5)
        p = _softmax(scores, axis=-1)
        o = torch.einsum("bhqk,bhkd->bhqd", p, v_cache)
        return (lambda x, *d: x.permute(*d))(o, 0, 2, 1, 3).reshape(B, Sq, H * Dh) @ wo

    def _B_ref(x, w1, b1, w2, b2):
        h = torch.einsum("bsd,df->bsf", x, w1) + b1
        zero = torch.zeros_like(h)
        r = torch.where(h > zero, h, zero)
        h = r * r
        out = torch.einsum("bsf,fd->bsd", h, w2) + b2
        return out

    x = A_x
    h = x + _A_ref(_layernorm(x, axis=-1), A_k_cache, A_v_cache, A_wq, A_wo)
    h2 = h + _B_ref(_layernorm(h, axis=-1), B_w1, B_b1, B_w2, B_b2)
    return h2
```

```cpp
#include <cuda_runtime.h>
#include <cuda_bf16.h>
#include <stdint.h>

namespace {

constexpr int DM = 448, NH = 16, SK = 4096, DH = 256, FF = 1792;
constexpr int NCTA = 128;
constexpr int CHUNK = 32768;
constexpr int NCH = SK / 64;
constexpr int NS = 5;
constexpr int DRY_AT = NCH - 10;
#define TRIG_BACK 3
constexpr int TRIG_AT = NCH - TRIG_BACK;
constexpr int NTHREADS = 13 * 32;
constexpr int SPIN_LIMIT = 1 << 20;

constexpr int SM_RING = 0;
constexpr int SM_WX = 3 * CHUNK;
constexpr int SM_WD = NS * CHUNK;
constexpr int SM_P = SM_WD + 32768;
constexpr int SM_RED = SM_P + 8192;
constexpr int SM_XN = SM_RED + 8 * 8 * 68 * 4;
constexpr int SM_Q = SM_XN + 8 * 456 * 2;
constexpr int SM_STAT = SM_Q + 512;
constexpr int SM_BAR = SM_STAT + 64;
constexpr int SM_TOTAL = SM_BAR + 128;
constexpr int BAR_FULL = SM_BAR, BAR_EMPTY = SM_BAR + 8 * NS, BAR_DRY = SM_BAR + 16 * NS, BAR_TRIG = BAR_DRY + 8;
static_assert(SM_TOTAL <= 232448, "shared memory budget");
static_assert((2 * NCH - 5) % NS == 3 && TRIG_BACK <= 4, "stages 3-4 must be drained at the trigger");

__device__ uint32_t g_q[NCTA * 128];
__device__ uint32_t g_o[NH * 8 * 128];
__device__ uint32_t g_part[7 * 8 * 2 * 16 * 32];
__device__ uint32_t g_h[4 * 8 * 224];
__device__ uint32_t g_r[2 * 56 * 4 * 16];
__device__ uint32_t g_near_done;

#define PROF_AT(cond, slot) do { } while (0)

__device__ __forceinline__ void mbar_init(uint32_t bar, uint32_t count) {
    asm volatile("mbarrier.init.shared::cta.b64 [%0], %1;" ::"r"(bar), "r"(count) : "memory");
}
__device__ __forceinline__ void mbar_arrive(uint32_t bar) {
    asm volatile("mbarrier.arrive.shared::cta.b64 _, [%0];" ::"r"(bar) : "memory");
}
__device__ __forceinline__ void mbar_expect_tx(uint32_t bar, uint32_t bytes) {
    asm volatile("mbarrier.arrive.expect_tx.shared::cta.b64 _, [%0], %1;" ::"r"(bar), "r"(bytes) : "memory");
}
__device__ __forceinline__ void mbar_wait(uint32_t bar, uint32_t parity) {
    uint32_t done;
    int it = 0;
    do {
        asm volatile("{\n.reg .pred p;\nmbarrier.try_wait.parity.shared::cta.b64 p, [%1], %2;\nselp.u32 %0, 1, 0, p;\n}"
                     : "=r"(done) : "r"(bar), "r"(parity) : "memory");
    } while (!done && ++it < SPIN_LIMIT);
}
__device__ __forceinline__ void bulk_load(uint32_t dst, const void* src, uint32_t bytes, uint32_t bar, uint64_t pol) {
    asm volatile("cp.async.bulk.shared::cluster.global.mbarrier::complete_tx::bytes.L2::cache_hint [%0], [%1], %2, [%3], %4;"
                 ::"r"(dst), "l"(src), "r"(bytes), "r"(bar), "l"(pol) : "memory");
}
__device__ __forceinline__ void cp16(uint32_t dst, const void* src, uint32_t on) {
    asm volatile("{\n.reg .pred p;\nsetp.ne.u32 p, %2, 0;\n@p cp.async.cg.shared.global [%0], [%1], 16;\n}"
                 ::"r"(dst), "l"(src), "r"(on) : "memory");
}
__device__ __forceinline__ void cp_commit() { asm volatile("cp.async.commit_group;" ::: "memory"); }
template <int N> __device__ __forceinline__ void cp_wait() { asm volatile("cp.async.wait_group %0;" ::"n"(N) : "memory"); }
__device__ __forceinline__ void bar_sync(int id, int n) { asm volatile("bar.sync %0, %1;" ::"r"(id), "r"(n) : "memory"); }

__device__ __forceinline__ void ldsm4(uint32_t (&r)[4], uint32_t a) {
    asm volatile("ldmatrix.sync.aligned.m8n8.x4.shared.b16 {%0,%1,%2,%3}, [%4];"
                 : "=r"(r[0]), "=r"(r[1]), "=r"(r[2]), "=r"(r[3]) : "r"(a) : "memory");
}
__device__ __forceinline__ void ldsm4t(uint32_t (&r)[4], uint32_t a) {
    asm volatile("ldmatrix.sync.aligned.m8n8.x4.trans.shared.b16 {%0,%1,%2,%3}, [%4];"
                 : "=r"(r[0]), "=r"(r[1]), "=r"(r[2]), "=r"(r[3]) : "r"(a) : "memory");
}
__device__ __forceinline__ void mma(float (&c)[4], const uint32_t (&a)[4], uint32_t b0, uint32_t b1) {
    asm volatile("mma.sync.aligned.m16n8k16.row.col.f32.bf16.bf16.f32 {%0,%1,%2,%3}, {%4,%5,%6,%7}, {%8,%9}, {%0,%1,%2,%3};"
                 : "+f"(c[0]), "+f"(c[1]), "+f"(c[2]), "+f"(c[3])
                 : "r"(a[0]), "r"(a[1]), "r"(a[2]), "r"(a[3]), "r"(b0), "r"(b1));
}
__device__ __forceinline__ uint32_t lds32(uint32_t a) {
    uint32_t v;
    asm volatile("ld.shared.u32 %0, [%1];" : "=r"(v) : "r"(a) : "memory");
    return v;
}
__device__ __forceinline__ float2 lds64f(uint32_t a) {
    float2 v;
    asm volatile("ld.shared.v2.f32 {%0,%1}, [%2];" : "=f"(v.x), "=f"(v.y) : "r"(a) : "memory");
    return v;
}
__device__ __forceinline__ uint4 lds128(uint32_t a) {
    uint4 v;
    asm volatile("ld.shared.v4.u32 {%0,%1,%2,%3}, [%4];" : "=r"(v.x), "=r"(v.y), "=r"(v.z), "=r"(v.w) : "r"(a) : "memory");
    return v;
}
__device__ __forceinline__ void sts16(uint32_t a, uint32_t v) {
    asm volatile("st.shared.u16 [%0], %1;" ::"r"(a), "h"((unsigned short)v) : "memory");
}
__device__ __forceinline__ void sts32(uint32_t a, uint32_t v) {
    asm volatile("st.shared.u32 [%0], %1;" ::"r"(a), "r"(v) : "memory");
}
__device__ __forceinline__ void sts32f(uint32_t a, float v) {
    asm volatile("st.shared.f32 [%0], %1;" ::"r"(a), "f"(v) : "memory");
}
__device__ __forceinline__ void sts128(uint32_t a, uint4 v) {
    asm volatile("st.shared.v4.u32 [%0], {%1,%2,%3,%4};" ::"r"(a), "r"(v.x), "r"(v.y), "r"(v.z), "r"(v.w) : "memory");
}

__device__ __forceinline__ void xld32(uint32_t& v, const uint32_t* p, uint32_t on) {
    asm volatile("{\n.reg .pred p;\nsetp.ne.u32 p, %2, 0;\n@p ld.relaxed.gpu.global.u32 %0, [%1];\n}"
                 : "+r"(v) : "l"(p), "r"(on) : "memory");
}
__device__ __forceinline__ void xld128(uint4& v, const uint32_t* p, uint32_t on) {
    asm volatile("{\n.reg .pred p;\nsetp.ne.u32 p, %5, 0;\n@p ld.relaxed.gpu.global.v4.u32 {%0,%1,%2,%3}, [%4];\n}"
                 : "+r"(v.x), "+r"(v.y), "+r"(v.z), "+r"(v.w) : "l"(p), "r"(on) : "memory");
}
__device__ __forceinline__ void xst32(uint32_t* p, uint32_t v) {
    asm volatile("st.relaxed.gpu.global.u32 [%0], %1;" ::"l"(p), "r"(v) : "memory");
}
__device__ __forceinline__ void xst64(uint32_t* p, uint32_t a, uint32_t b) {
    asm volatile("st.relaxed.gpu.global.v2.u32 [%0], {%1,%2};" ::"l"(p), "r"(a), "r"(b) : "memory");
}
__device__ __forceinline__ uint32_t missing(const uint4& v) { return v.x == 0 || v.y == 0 || v.z == 0 || v.w == 0; }
__device__ __forceinline__ uint32_t enc(uint32_t bits, uint32_t mask) {
    return (bits == 0xffffffffu ? 0x80008000u : ~bits) & mask;
}

__device__ __forceinline__ float bf_round(float v) { return __bfloat162float(__float2bfloat16_rn(v)); }
__device__ __forceinline__ uint32_t pack_bf(float lo, float hi) {
    uint32_t r;
    asm("cvt.rn.bf16x2.f32 %0, %1, %2;" : "=r"(r) : "f"(hi), "f"(lo));
    return r;
}
__device__ __forceinline__ float bf_lo(uint32_t w) { return __uint_as_float(w << 16); }
__device__ __forceinline__ float bf_hi(uint32_t w) { return __uint_as_float(w & 0xffff0000u); }

__device__ __forceinline__ void layernorm_row(const uint32_t (&w)[7], uint32_t dst, int lane) {
    const float shift = bf_lo(__shfl_sync(0xffffffffu, w[0], 0));
    float s = 0.f, ss = 0.f;
#pragma unroll
    for (int i = 0; i < 7; i++) {
        const float a = bf_lo(w[i]) - shift, b = bf_hi(w[i]) - shift;
        s += a + b;
        ss = fmaf(a, a, fmaf(b, b, ss));
    }
#pragma unroll
    for (int o = 16; o; o >>= 1) {
        s += __shfl_xor_sync(0xffffffffu, s, o);
        ss += __shfl_xor_sync(0xffffffffu, ss, o);
    }
    const float md = s * (1.f / DM);
    const float mean = bf_round(shift + md);
    const float var = bf_round(fmaxf(ss * (1.f / DM) - md * md, 0.f));
    const float inv = 1.f / bf_round(sqrtf(bf_round(var + 1e-5f)));
#pragma unroll
    for (int i = 0; i < 7; i++) {
        const float a = bf_round(bf_lo(w[i]) - mean) * inv, b = bf_round(bf_hi(w[i]) - mean) * inv;
        sts32(dst + (i * 32 + lane) * 4, pack_bf(a, b));
    }
}

__device__ __forceinline__ void load_w448(uint32_t dst, const __nv_bfloat16* w, int ld, int ew, int lane, uint32_t on) {
#pragma unroll
    for (int i = 0; i < 8; i++) {
        const int row = ew * 64 + i * 8 + (lane >> 2), ch = lane & 3;
        cp16(dst + row * 64 + ((ch ^ ((row >> 1) & 3)) << 4), w + (size_t)row * ld + ch * 8, on && ew < 7);
    }
}
__device__ __forceinline__ void frags_w448(uint32_t (&a)[8][4], uint32_t src, int ew, int lane) {
    const int r = lane & 7, mi = lane >> 3;
    const uint32_t base = src + ((ew < 7 ? ew : 0) * 64 + (mi >> 1) * 8 + r) * 64;
#pragma unroll
    for (int ks = 0; ks < 4; ks++)
#pragma unroll
        for (int mt = 0; mt < 2; mt++)
            ldsm4t(a[ks * 2 + mt], base + ks * 1024 + (((2 * mt + (mi & 1)) ^ (r >> 1)) << 4));
}
__device__ __forceinline__ float2 gemv448(const uint32_t (&a)[8][4], uint32_t sb, int ew, int lane, int et) {
    const int g = lane >> 2, t = lane & 3;
    bar_sync(2, 256);
    if (ew < 7) {
        float c[4][4] = {};
        const uint32_t xb = sb + SM_XN + (g * 228 + ew * 32 + t) * 4;
#pragma unroll
        for (int ks = 0; ks < 4; ks++) {
            const uint32_t b0 = lds32(xb + ks * 32), b1 = lds32(xb + ks * 32 + 16);
            mma(c[(ks & 1) * 2], a[ks * 2], b0, b1);
            mma(c[(ks & 1) * 2 + 1], a[ks * 2 + 1], b0, b1);
        }
        const uint32_t rb = sb + SM_RED + (ew * 288 + t * 72 + g) * 4;
#pragma unroll
        for (int mt = 0; mt < 2; mt++) {
            sts32f(rb + mt * 64, c[mt][0] + c[2 + mt][0]);
            sts32f(rb + mt * 64 + 144, c[mt][1] + c[2 + mt][1]);
            sts32f(rb + mt * 64 + 32, c[mt][2] + c[2 + mt][2]);
            sts32f(rb + mt * 64 + 176, c[mt][3] + c[2 + mt][3]);
        }
    }
    bar_sync(2, 256);
    float2 acc = make_float2(0.f, 0.f);
    if (et < 128) {
        const uint32_t rb = sb + SM_RED + ((et >> 4) * 36 + (et & 15) * 2) * 4;
#pragma unroll
        for (int w = 0; w < 7; w++) {
            const float2 v = lds64f(rb + w * 1152);
            acc.x += v.x;
            acc.y += v.y;
        }
    }
    return acc;
}

struct Params {
    const __nv_bfloat16 *x, *k, *v, *wq, *wo, *w1, *b1, *w2, *b2;
    __nv_bfloat16* out;
};

__global__ void __launch_bounds__(NTHREADS, 1) fused_decode_kernel(const Params p) {
    extern __shared__ __align__(1024) unsigned char smem[];
    const uint32_t sb = (uint32_t)__cvta_generic_to_shared(smem);
    const int tid = threadIdx.x, warp = tid >> 5, lane = tid & 31;
    const int c = blockIdx.x;
    const char* kbase = (const char*)p.k + (size_t)c * (SK * DH * 2);
    const char* vbase = (const char*)p.v + (size_t)c * (SK * DH * 2);

    if (warp == 4) {
        uint64_t pol = 0;
        if (lane == 0) {
            PROF_AT(true, 0);
#pragma unroll
            for (int s = 0; s < NS; s++) {
                mbar_init(sb + BAR_FULL + 8 * s, 1);
                mbar_init(sb + BAR_EMPTY + 8 * s, 4);
            }
            mbar_init(sb + BAR_DRY, 4);
            mbar_init(sb + BAR_TRIG, 4);
            asm volatile("fence.mbarrier_init.release.cluster;" ::: "memory");
            asm volatile("createpolicy.fractional.L2::evict_first.b64 %0, 1.0;" : "=l"(pol));
#pragma unroll
            for (int s = 0; s < NS; s++) {
                mbar_expect_tx(sb + BAR_FULL + 8 * s, CHUNK);
                bulk_load(sb + SM_RING + s * CHUNK, kbase + s * CHUNK, CHUNK, sb + BAR_FULL + 8 * s, pol);
            }
        }
        __syncthreads();
        if (lane == 0) {
            int s = 0;
            uint32_t ph = 0;
#pragma unroll 1
            for (int i = NS; i < 2 * NCH; i++) {
                const char* src = i < NCH ? kbase + (size_t)i * CHUNK : vbase + (size_t)(i - NCH) * CHUNK;
                mbar_wait(sb + BAR_EMPTY + 8 * s, ph);
                mbar_expect_tx(sb + BAR_FULL + 8 * s, CHUNK);
                bulk_load(sb + SM_RING + s * CHUNK, src, CHUNK, sb + BAR_FULL + 8 * s, pol);
                if (++s == NS) { s = 0; ph ^= 1; }
            }
        }
    } else if (warp < 4) {
        __syncthreads();
        const int g = lane >> 2, t = lane & 3, r = lane & 7, mi = lane >> 3;
        {
            uint32_t* slot = g_q + c * 128 + tid;
            uint32_t w = 0;
            int it = 0;
            do {
                xld32(w, slot, 1);
            } while (w == 0 && ++it < SPIN_LIMIT);
            xst32(slot, 0);
            sts32(sb + SM_Q + tid * 4, ~w);
        }
        bar_sync(1, 128);
        PROF_AT(tid == 0, 2);
        int s = 0;
        uint32_t ph = 0;
        float rmax = -INFINITY;
        {
            uint32_t qf[32];
#pragma unroll
            for (int i = 0; i < 32; i++) qf[i] = lds32(sb + SM_Q + ((i ^ g) * 4 + t) * 4);
            uint32_t off[4];
#pragma unroll
            for (int i = 0; i < 4; i++)
                off[i] = sb + SM_RING + (warp * 16 + (mi & 1) * 8 + r) * 512 + (((2 * i + (mi >> 1)) ^ r) << 4);
            const bool owner = t == (g >> 1);
            uint32_t pdst = sb + SM_P + (t * 16 + warp * 4 + (g & 1)) * 2;
#pragma unroll 1
            for (int i = 0; i < NCH; i++) {
                mbar_wait(sb + BAR_FULL + 8 * s, ph);
                float acc[4][4] = {};
#pragma unroll
                for (int ks = 0; ks < 16; ks++) {
                    uint32_t a[4];
                    ldsm4(a, off[ks & 3] + s * CHUNK + (ks >> 2) * 128);
                    mma(acc[ks & 3], a, qf[2 * ks], qf[2 * ks + 1]);
                }
                __syncwarp();
                if (lane == 0) mbar_arrive(sb + BAR_EMPTY + 8 * s);
                float v[4];
#pragma unroll
                for (int e = 0; e < 4; e++) v[e] = (acc[0][e] + acc[1][e]) + (acc[2][e] + acc[3][e]);
                const float lo = (g & 1) ? v[1] : v[0], hi = (g & 1) ? v[3] : v[2];
                const uint32_t sc = pack_bf(bf_round(lo) * 0.0625f, bf_round(hi) * 0.0625f);
                if (owner) {
                    sts16(pdst, sc & 0xffffu);
                    sts16(pdst + 4, sc >> 16);
                    rmax = fmaxf(rmax, fmaxf(bf_lo(sc), bf_hi(sc)));
                }
                pdst += 128;
                if (++s == NS) { s = 0; ph ^= 1; }
            }
        }
        PROF_AT(tid == 0, 3);
        {
#pragma unroll
            for (int o = 16; o; o >>= 1) rmax = fmaxf(rmax, __shfl_xor_sync(0xffffffffu, rmax, o));
            if (lane == 0) sts32f(sb + SM_STAT + warp * 4, rmax);
            bar_sync(1, 128);
            const uint4 mx = lds128(sb + SM_STAT);
            const float m = fmaxf(fmaxf(__uint_as_float(mx.x), __uint_as_float(mx.y)),
                                  fmaxf(__uint_as_float(mx.z), __uint_as_float(mx.w)));
            float e[32];
            float sum = 0.f;
#pragma unroll
            for (int i = 0; i < 4; i++) {
                const uint4 w = lds128(sb + SM_P + (i * 128 + tid) * 16);
                const uint32_t ww[4] = {w.x, w.y, w.z, w.w};
#pragma unroll
                for (int j = 0; j < 4; j++) {
                    e[i * 8 + 2 * j] = __expf(bf_lo(ww[j]) - m);
                    e[i * 8 + 2 * j + 1] = __expf(bf_hi(ww[j]) - m);
                    sum += e[i * 8 + 2 * j] + e[i * 8 + 2 * j + 1];
                }
            }
#pragma unroll
            for (int o = 16; o; o >>= 1) sum += __shfl_xor_sync(0xffffffffu, sum, o);
            if (lane == 0) sts32f(sb + SM_STAT + 16 + warp * 4, sum);
            bar_sync(1, 128);
            const uint4 sm = lds128(sb + SM_STAT + 16);
            const float inv = 1.f / ((__uint_as_float(sm.x) + __uint_as_float(sm.y)) +
                                     (__uint_as_float(sm.z) + __uint_as_float(sm.w)));
#pragma unroll
            for (int i = 0; i < 4; i++) {
                uint4 w;
                w.x = pack_bf(e[i * 8 + 0] * inv, e[i * 8 + 1] * inv);
                w.y = pack_bf(e[i * 8 + 2] * inv, e[i * 8 + 3] * inv);
                w.z = pack_bf(e[i * 8 + 4] * inv, e[i * 8 + 5] * inv);
                w.w = pack_bf(e[i * 8 + 6] * inv, e[i * 8 + 7] * inv);
                sts128(sb + SM_P + (i * 128 + tid) * 16, w);
            }
            bar_sync(1, 128);
        }
        {
            uint32_t off[4];
#pragma unroll
            for (int i = 0; i < 4; i++)
                off[i] = sb + SM_RING + ((mi >> 1) * 8 + r) * 512 + warp * 128 + (((2 * i + (mi & 1)) ^ r) << 4);
            const uint32_t pmask = t == (g >> 1) ? ((g & 1) ? 0xffff0000u : 0x0000ffffu) : 0u;
            uint32_t* odst = g_o + ((c & 15) * 8 + (c >> 4)) * 128 + (warp * 2 + (t >> 1)) * 16 + (g >> 1) * 4 +
                             (t & 1) * 2 + (g & 1);
#pragma unroll 1
            for (int pass = 0; pass < 2; pass++) {
                int n = pass * NCH;
                asm volatile("" : "+r"(n));
                float acc[4][4] = {};
                uint32_t psrc = sb + SM_P + t * 32;
#pragma unroll 1
                for (int i = 0; i < n; i++) {
                    const uint4 p0 = lds128(psrc), p1 = lds128(psrc + 16);
                    const uint32_t pb[8] = {p0.x & pmask, p0.y & pmask, p0.z & pmask, p0.w & pmask,
                                            p1.x & pmask, p1.y & pmask, p1.z & pmask, p1.w & pmask};
                    psrc += 128;
                    mbar_wait(sb + BAR_FULL + 8 * s, ph);
#pragma unroll
                    for (int ks = 0; ks < 4; ks++)
#pragma unroll
                        for (int T = 0; T < 4; T++) {
                            uint32_t a[4];
                            ldsm4t(a, off[T] + s * CHUNK + ks * 8192);
                            mma(acc[T], a, pb[2 * ks], pb[2 * ks + 1]);
                        }
                    __syncwarp();
                    if (lane == 0) {
                        mbar_arrive(sb + BAR_EMPTY + 8 * s);
                        if (i == DRY_AT) mbar_arrive(sb + BAR_DRY);
                        if (i == TRIG_AT) mbar_arrive(sb + BAR_TRIG);
                    }
                    if (++s == NS) { s = 0; ph ^= 1; }
                }
                PROF_AT(tid == 0 && pass, 4);
                float ev[4], od[4];
#pragma unroll
                for (int T = 0; T < 4; T++) {
                    ev[T] = acc[T][0] + acc[T][3];
                    od[T] = acc[T][1] + acc[T][2];
                }
                ev[0] += __shfl_xor_sync(0xffffffffu, ev[1], 1);
                od[0] += __shfl_xor_sync(0xffffffffu, od[1], 1);
                ev[2] += __shfl_xor_sync(0xffffffffu, ev[3], 1);
                od[2] += __shfl_xor_sync(0xffffffffu, od[3], 1);
                ev[0] += __shfl_xor_sync(0xffffffffu, ev[2], 2);
                od[0] += __shfl_xor_sync(0xffffffffu, od[2], 2);
                const float other = __shfl_xor_sync(0xffffffffu, (g & 1) ? ev[0] : od[0], 4);
                const uint32_t w = (g & 1) ? pack_bf(other, od[0]) : pack_bf(ev[0], other);
                xst32(odst, enc(w, n ? 0xffffffffu : 0u));
            }
            PROF_AT(tid == 0, 5);
        }
    } else {
        const int ew = warp - 5, et = tid - 160;
        const int g = lane >> 2, t = lane & 3, r = lane & 7, mi = lane >> 3;
        {
            load_w448(sb + SM_WD, p.wq + c * 32, NH * DH, ew, lane, 1);
            cp_commit();
            uint32_t w[7];
#pragma unroll
            for (int i = 0; i < 7; i++) w[i] = __ldg((const uint32_t*)p.x + ew * 224 + i * 32 + lane);
            __syncthreads();
            layernorm_row(w, sb + SM_XN + ew * 912, lane);
            cp_wait<0>();
            __syncwarp();
            uint32_t a[8][4];
            frags_w448(a, sb + SM_WD, ew, lane);
            const float2 q = gemv448(a, sb, ew, lane, et);
            if (et < 128)
                xst32(g_q + ((et >> 4) * 16 + (c >> 3)) * 128 + (c & 7) * 16 + (et & 15), enc(pack_bf(q.x, q.y), 0xffffffffu));
            PROF_AT(et == 0, 1);
        }
        const int hh = c / 7, jj = c - hh * 7;
        const int rb = hh >> 1, rh = hh & 1;
        const bool is_f1 = c < 56;
        const int cg = (c - 56) % 28, half = (c - 56) / 28;
        uint32_t xres0 = 0, xres1 = 0, bias = 0;
        if (c < 112) {
            const uint2 xr = __ldg((const uint2*)(p.x + rb * DM + jj * 64 + rh * 32) + (lane & 7));
            xres0 = xr.x;
            xres1 = xr.y;
            bias = is_f1 ? __ldg((const uint32_t*)p.b1 + c * 16 + (et & 15)) : __ldg((const uint32_t*)p.b2 + cg * 8 + (et & 7));
        }
#pragma unroll 1
        for (int pass = 0; pass < 2; pass++) {
            uint32_t live = pass;
            asm volatile("" : "+r"(live));
            const uint32_t mask = 0u - live;
            if (ew == 0) {
                mbar_wait(sb + (live ? BAR_TRIG : BAR_DRY), 0);
                if (live && lane == 0) {
                    uint32_t seen;
                    asm volatile("atom.acq_rel.gpu.global.add.u32 %0, [%1], 1;" : "=r"(seen) : "l"(&g_near_done) : "memory");
                    const uint32_t target = (seen & ~(uint32_t)(NCTA - 1)) + NCTA;
                    int it = 0;
                    if (c < 112)
                        for (seen++; (int)(seen - target) < 0 && ++it < SPIN_LIMIT;) {
                            __nanosleep(64);
                            asm volatile("ld.acquire.gpu.global.u32 %0, [%1];" : "=r"(seen) : "l"(&g_near_done) : "memory");
                        }
                }
            }
            if (c >= 112) continue;
            bar_sync(2, 256);
            PROF_AT(et == 0 && live, 6);
#pragma unroll
            for (int i = 0; i < 8; i++) {
                const int row = ew * 32 + i * 4 + mi;
                cp16(sb + SM_WD + row * 128 + ((r ^ (row & 7)) << 4), p.wo + (size_t)(hh * 256 + row) * DM + jj * 64 + r * 8, live);
            }
            cp_commit();
            if (is_f1) {
                load_w448(sb + SM_WX, p.w1 + c * 32, FF, ew, lane, live);
            } else {
#pragma unroll
                for (int i = 0; i < 14; i++) {
                    const int row = ew * 224 + i * 16 + (lane >> 1), ch = lane & 1;
                    cp16(sb + SM_WX + row * 32 + ((ch ^ ((row >> 2) & 1)) << 4), p.w2 + (size_t)row * DM + cg * 16 + ch * 8, live);
                }
            }
            cp_commit();
            {
                cp_wait<1>();
                __syncwarp();
                uint32_t a[8][4];
                const uint32_t base = sb + SM_WD + (ew * 32 + (mi >> 1) * 8 + r) * 128;
#pragma unroll
                for (int ks = 0; ks < 2; ks++)
#pragma unroll
                    for (int mt = 0; mt < 4; mt++)
                        ldsm4t(a[ks * 4 + mt], base + ks * 2048 + (((2 * mt + (mi & 1)) ^ r) << 4));
                PROF_AT(et == 0 && live, 7);
                uint4 o = make_uint4(0, 0, 0, 0);
                const uint32_t* src = g_o + (hh * 8 + g) * 128 + ew * 16 + t * 4;
                int it = 0;
                do {
                    xld128(o, src, live);
                } while (live && missing(o) && ++it < SPIN_LIMIT);
                __syncwarp();
                PROF_AT(et == 0 && live, 8);
                float acc[4][4] = {};
#pragma unroll
                for (int mt = 0; mt < 4; mt++) mma(acc[mt], a[mt], ~o.x, ~o.y);
#pragma unroll
                for (int mt = 0; mt < 4; mt++) mma(acc[mt], a[4 + mt], ~o.z, ~o.w);
                const uint32_t wb = sb + SM_RED + (ew * 544 + t * 136 + g) * 4;
#pragma unroll
                for (int mt = 0; mt < 4; mt++) {
                    sts32f(wb + mt * 64, acc[mt][0]);
                    sts32f(wb + mt * 64 + 272, acc[mt][1]);
                    sts32f(wb + mt * 64 + 32, acc[mt][2]);
                    sts32f(wb + mt * 64 + 304, acc[mt][3]);
                }
                bar_sync(2, 256);
                float2 sum = make_float2(0.f, 0.f);
#pragma unroll
                for (int w = 0; w < 8; w++) {
                    const float2 v = lds64f(sb + SM_RED + (w * 544 + ew * 68 + lane * 2) * 4);
                    sum.x += v.x;
                    sum.y += v.y;
                }
                xst64(g_part + (((jj * 8 + ew) * 2 + (lane >> 4)) * 16 + hh) * 32 + (lane & 15) * 2,
                      enc(__float_as_uint(sum.x), mask), enc(__float_as_uint(sum.y), mask));
            }
            if (ew == 0) {
                uint4 v[4];
                const uint32_t* src = g_part + ((jj * 8 + rb) * 2 + rh) * 512 + lane * 4;
                uint32_t miss = live ? 15u : 0u;
#pragma unroll
                for (int i = 0; i < 4; i++) v[i] = make_uint4(0, 0, 0, 0);
                int it = 0;
                do {
#pragma unroll
                    for (int i = 0; i < 4; i++) xld128(v[i], src + i * 128, miss & (1u << i));
#pragma unroll
                    for (int i = 0; i < 4; i++)
                        if (!missing(v[i])) miss &= ~(1u << i);
                } while (miss && ++it < SPIN_LIMIT);
                __syncwarp();
                float f[4];
                f[0] = (__uint_as_float(~v[0].x) + __uint_as_float(~v[1].x)) + (__uint_as_float(~v[2].x) + __uint_as_float(~v[3].x));
                f[1] = (__uint_as_float(~v[0].y) + __uint_as_float(~v[1].y)) + (__uint_as_float(~v[2].y) + __uint_as_float(~v[3].y));
                f[2] = (__uint_as_float(~v[0].z) + __uint_as_float(~v[1].z)) + (__uint_as_float(~v[2].z) + __uint_as_float(~v[3].z));
                f[3] = (__uint_as_float(~v[0].w) + __uint_as_float(~v[1].w)) + (__uint_as_float(~v[2].w) + __uint_as_float(~v[3].w));
#pragma unroll
                for (int i = 0; i < 4; i++) f[i] += __shfl_xor_sync(0xffffffffu, f[i], 8);
#pragma unroll
                for (int i = 0; i < 4; i++) f[i] += __shfl_xor_sync(0xffffffffu, f[i], 16);
                const uint32_t h0 = pack_bf(bf_lo(xres0) + bf_round(f[0]), bf_hi(xres0) + bf_round(f[1]));
                const uint32_t h1 = pack_bf(bf_lo(xres1) + bf_round(f[2]), bf_hi(xres1) + bf_round(f[3]));
                xst64(g_h + (mi * 8 + rb) * 224 + jj * 32 + rh * 16 + r * 2, enc(h0, mask), enc(h1, mask));
                PROF_AT(et == 0 && live, 9);
            }
            cp_wait<0>();
            __syncwarp();
            if (is_f1) {
                uint32_t a[8][4];
                frags_w448(a, sb + SM_WX, ew, lane);
                uint32_t w[7];
#pragma unroll
                for (int i = 0; i < 7; i++) w[i] = 0;
                const uint32_t* src = g_h + ((c & 3) * 8 + ew) * 224 + lane;
                int it = 0;
                uint32_t miss;
                do {
                    miss = 0;
#pragma unroll
                    for (int i = 0; i < 7; i++) xld32(w[i], src + i * 32, live && w[i] == 0);
#pragma unroll
                    for (int i = 0; i < 7; i++) miss |= w[i] == 0;
                } while (live && miss && ++it < SPIN_LIMIT);
                __syncwarp();
                PROF_AT(et == 0 && live, 10);
#pragma unroll
                for (int i = 0; i < 7; i++) w[i] = ~w[i];
                layernorm_row(w, sb + SM_XN + ew * 912, lane);
                const float2 u = gemv448(a, sb, ew, lane, et);
                if (et < 128) {
                    const float u0 = bf_round(bf_round(u.x) + bf_lo(bias)), u1 = bf_round(bf_round(u.y) + bf_hi(bias));
                    const float r0 = u0 > 0.f ? u0 : 0.f, r1 = u1 > 0.f ? u1 : 0.f;
                    const int b = et >> 4, pr = et & 15;
                    xst32(g_r + (((b >> 2) * 56 + c) * 4 + (b & 3)) * 16 + (pr & 3) * 4 + (pr >> 2),
                          enc(pack_bf(r0 * r0, r1 * r1), mask));
                }
                PROF_AT(et == 0 && live, 11);
            } else {
                uint32_t a[14][4];
                const uint32_t base = sb + SM_WX + (ew * 224 + (mi >> 1) * 8 + r) * 32 + (((mi & 1) ^ (r >> 2)) << 4);
#pragma unroll
                for (int ks = 0; ks < 14; ks++) ldsm4t(a[ks], base + ks * 512);
                uint32_t hres = 0;
                const uint32_t* hsrc = g_h + ((c & 3) * 8 + half * 4 + mi) * 224 + cg * 8 + r;
                int it = 0;
                do {
                    xld32(hres, hsrc, live);
                } while (live && hres == 0 && ++it < SPIN_LIMIT);
                __syncwarp();
                PROF_AT(et == 0 && live, 10);
                uint4 v[7];
                const uint32_t* src = g_r + (half * 56 + ew * 7) * 64 + (lane & 15) * 4;
                uint32_t miss = (live && lane < 16) ? 127u : 0u;
#pragma unroll
                for (int i = 0; i < 7; i++) v[i] = make_uint4(~0u, ~0u, ~0u, ~0u);
                it = 0;
                do {
#pragma unroll
                    for (int i = 0; i < 7; i++) xld128(v[i], src + i * 64, miss & (1u << i));
#pragma unroll
                    for (int i = 0; i < 7; i++)
                        if (!missing(v[i])) miss &= ~(1u << i);
                } while (miss && ++it < SPIN_LIMIT);
                __syncwarp();
                PROF_AT(et == 0 && live, 11);
                float acc[4][4] = {};
#pragma unroll
                for (int i = 0; i < 7; i++) {
                    mma(acc[(2 * i) & 3], a[2 * i], ~v[i].x, ~v[i].y);
                    mma(acc[(2 * i + 1) & 3], a[2 * i + 1], ~v[i].z, ~v[i].w);
                }
                if (t < 2) {
                    const uint32_t wb = sb + SM_XN + (ew * 80 + t * 40 + g) * 4;
                    sts32f(wb, (acc[0][0] + acc[1][0]) + (acc[2][0] + acc[3][0]));
                    sts32f(wb + 80, (acc[0][1] + acc[1][1]) + (acc[2][1] + acc[3][1]));
                    sts32f(wb + 32, (acc[0][2] + acc[1][2]) + (acc[2][2] + acc[3][2]));
                    sts32f(wb + 112, (acc[0][3] + acc[1][3]) + (acc[2][3] + acc[3][3]));
                }
                bar_sync(2, 256);
                if (ew == 0) {
                    float2 sum = make_float2(0.f, 0.f);
#pragma unroll
                    for (int w = 0; w < 8; w++) {
                        const float2 x = lds64f(sb + SM_XN + (w * 80 + mi * 20 + r * 2) * 4);
                        sum.x += x.x;
                        sum.y += x.y;
                    }
                    hres = ~hres;
                    const float y0 = bf_round(bf_round(sum.x) + bf_lo(bias)), y1 = bf_round(bf_round(sum.y) + bf_hi(bias));
                    if (live)
                        ((uint32_t*)p.out)[(half * 4 + mi) * 224 + cg * 8 + r] = pack_bf(bf_lo(hres) + y0, bf_hi(hres) + y1);
                    PROF_AT(et == 0 && live, 12);
                }
            }
            if (!live) {
                __threadfence();
                bar_sync(2, 256);
            }
        }
    }
}

}

extern "C" void kernel_launch(void* const* d_in, const int* in_sizes, int n_in, void* d_out, int out_size) {
    (void)in_sizes; (void)n_in; (void)out_size;
    Params p;
    p.x = (const __nv_bfloat16*)d_in[0];
    p.k = (const __nv_bfloat16*)d_in[1];
    p.v = (const __nv_bfloat16*)d_in[2];
    p.wq = (const __nv_bfloat16*)d_in[3];
    p.wo = (const __nv_bfloat16*)d_in[4];
    p.w1 = (const __nv_bfloat16*)d_in[6];
    p.b1 = (const __nv_bfloat16*)d_in[7];
    p.w2 = (const __nv_bfloat16*)d_in[8];
    p.b2 = (const __nv_bfloat16*)d_in[9];
    p.out = (__nv_bfloat16*)d_out;
    cudaFuncSetAttribute(fused_decode_kernel, cudaFuncAttributeMaxDynamicSharedMemorySize, SM_TOTAL);
    fused_decode_kernel<<<NCTA, NTHREADS, SM_TOTAL>>>(p);
}
```

```cpp
#include <cuda_runtime.h>
#include <cuda_bf16.h>
#include <stdint.h>

namespace {

constexpr int DM = 448, NH = 16, SK = 4096, DH = 256, FF = 1792;
constexpr int NCTA = 128;
constexpr int CHUNK = 32768;
constexpr int NCH = SK / 64;
constexpr int NS = 6;
#define DRY_CH 0
constexpr int DRY_AT = DRY_CH;
#define TRIG_BACK 5
#define TRIG_COUNT 112
constexpr int TRIG_AT = NCH - TRIG_BACK;
constexpr int FREE0_AT = NCH - 6;
constexpr int NTHREADS = 13 * 32;
constexpr int SPIN_LIMIT = 1 << 20;

constexpr int SM_RING = 0;
constexpr int SM_WX = 3 * CHUNK;
constexpr int SM_WQ = 5 * CHUNK;
constexpr int SM_WO = 2 * CHUNK;
constexpr int SM_P = NS * CHUNK;
constexpr int SM_RED = SM_P + 8192;
constexpr int SM_XN = SM_RED + 8 * 512 * 4;
constexpr int SM_Q = SM_XN + 8 * 456 * 2;
constexpr int SM_STAT = SM_Q + 512;
constexpr int SM_BAR = SM_STAT + 64;
constexpr int SM_TOTAL = SM_BAR + 192;
constexpr int BAR_FULL = SM_BAR, BAR_EMPTY = SM_BAR + 8 * NS, BAR_DRY = SM_BAR + 16 * NS, BAR_TRIG = BAR_DRY + 8,
              BAR_W1 = BAR_TRIG + 8, BAR_FREE0 = BAR_W1 + 8, BAR_WQ = BAR_FREE0 + 8,
              BAR_WQIN = BAR_WQ + 8, BAR_W0 = BAR_WQIN + 8;
static_assert(SM_TOTAL <= 232448, "shared memory budget");
static_assert((NCH + FREE0_AT) % NS == 2, "last chunk of the stage reused for wo");

struct Exchange {
    uint32_t q[NCTA * 128];
    uint32_t o[NH * 8 * 128];
    uint32_t part[7 * 16 * 16 * 32];
    uint32_t h[2 * 14 * 8 * 16];
    uint32_t r[2 * 56 * 4 * 16];
    uint32_t count[64];
};
__device__ __align__(128) Exchange g_x;

#define PROF_AT(cond, slot) do { } while (0)

__device__ __forceinline__ void mbar_init(uint32_t bar, uint32_t count) {
    asm volatile("mbarrier.init.shared::cta.b64 [%0], %1;" ::"r"(bar), "r"(count) : "memory");
}
__device__ __forceinline__ void mbar_arrive(uint32_t bar) {
    asm volatile("mbarrier.arrive.shared::cta.b64 _, [%0];" ::"r"(bar) : "memory");
}
__device__ __forceinline__ void mbar_expect_tx(uint32_t bar, uint32_t bytes) {
    asm volatile("mbarrier.arrive.expect_tx.shared::cta.b64 _, [%0], %1;" ::"r"(bar), "r"(bytes) : "memory");
}
__device__ __forceinline__ void mbar_wait(uint32_t bar, uint32_t parity) {
    uint32_t done;
    int it = 0;
    do {
        asm volatile("{\n.reg .pred p;\nmbarrier.try_wait.parity.shared::cta.b64 p, [%1], %2;\nselp.u32 %0, 1, 0, p;\n}"
                     : "=r"(done) : "r"(bar), "r"(parity) : "memory");
    } while (!done && ++it < SPIN_LIMIT);
}
__device__ __forceinline__ uint32_t mbar_test(uint32_t bar, uint32_t parity) {
    uint32_t done;
    asm volatile("{\n.reg .pred p;\nmbarrier.test_wait.parity.shared::cta.b64 p, [%1], %2;\nselp.u32 %0, 1, 0, p;\n}"
                 : "=r"(done) : "r"(bar), "r"(parity) : "memory");
    return done;
}
__device__ __forceinline__ void bulk_load(uint32_t dst, const void* src, uint32_t bytes, uint32_t bar, uint64_t pol) {
    asm volatile("cp.async.bulk.shared::cluster.global.mbarrier::complete_tx::bytes.L2::cache_hint [%0], [%1], %2, [%3], %4;"
                 ::"r"(dst), "l"(src), "r"(bytes), "r"(bar), "l"(pol) : "memory");
}
__device__ __forceinline__ void cp16(uint32_t dst, const void* src, uint32_t on) {
    asm volatile("{\n.reg .pred p;\nsetp.ne.u32 p, %2, 0;\n@p cp.async.cg.shared.global [%0], [%1], 16;\n}"
                 ::"r"(dst), "l"(src), "r"(on) : "memory");
}
__device__ __forceinline__ void cp_commit() { asm volatile("cp.async.commit_group;" ::: "memory"); }
template <int N> __device__ __forceinline__ void cp_wait() { asm volatile("cp.async.wait_group %0;" ::"n"(N) : "memory"); }
__device__ __forceinline__ void bar_sync(int id, int n) { asm volatile("bar.sync %0, %1;" ::"r"(id), "r"(n) : "memory"); }

__device__ __forceinline__ void ldsm4(uint32_t (&r)[4], uint32_t a) {
    asm volatile("ldmatrix.sync.aligned.m8n8.x4.shared.b16 {%0,%1,%2,%3}, [%4];"
                 : "=r"(r[0]), "=r"(r[1]), "=r"(r[2]), "=r"(r[3]) : "r"(a) : "memory");
}
__device__ __forceinline__ void ldsm4t(uint32_t (&r)[4], uint32_t a) {
    asm volatile("ldmatrix.sync.aligned.m8n8.x4.trans.shared.b16 {%0,%1,%2,%3}, [%4];"
                 : "=r"(r[0]), "=r"(r[1]), "=r"(r[2]), "=r"(r[3]) : "r"(a) : "memory");
}
__device__ __forceinline__ void mma(float (&c)[4], const uint32_t (&a)[4], uint32_t b0, uint32_t b1) {
    asm volatile("mma.sync.aligned.m16n8k16.row.col.f32.bf16.bf16.f32 {%0,%1,%2,%3}, {%4,%5,%6,%7}, {%8,%9}, {%0,%1,%2,%3};"
                 : "+f"(c[0]), "+f"(c[1]), "+f"(c[2]), "+f"(c[3])
                 : "r"(a[0]), "r"(a[1]), "r"(a[2]), "r"(a[3]), "r"(b0), "r"(b1));
}
__device__ __forceinline__ uint32_t lds32(uint32_t a) {
    uint32_t v;
    asm volatile("ld.shared.u32 %0, [%1];" : "=r"(v) : "r"(a) : "memory");
    return v;
}
__device__ __forceinline__ float2 lds64f(uint32_t a) {
    float2 v;
    asm volatile("ld.shared.v2.f32 {%0,%1}, [%2];" : "=f"(v.x), "=f"(v.y) : "r"(a) : "memory");
    return v;
}
__device__ __forceinline__ uint4 lds128(uint32_t a) {
    uint4 v;
    asm volatile("ld.shared.v4.u32 {%0,%1,%2,%3}, [%4];" : "=r"(v.x), "=r"(v.y), "=r"(v.z), "=r"(v.w) : "r"(a) : "memory");
    return v;
}
__device__ __forceinline__ void sts16(uint32_t a, uint32_t v) {
    asm volatile("st.shared.u16 [%0], %1;" ::"r"(a), "h"((unsigned short)v) : "memory");
}
__device__ __forceinline__ void sts32(uint32_t a, uint32_t v) {
    asm volatile("st.shared.u32 [%0], %1;" ::"r"(a), "r"(v) : "memory");
}
__device__ __forceinline__ void sts32f(uint32_t a, float v) {
    asm volatile("st.shared.f32 [%0], %1;" ::"r"(a), "f"(v) : "memory");
}
__device__ __forceinline__ void sts64f(uint32_t a, float x, float y) {
    asm volatile("st.shared.v2.f32 [%0], {%1,%2};" ::"r"(a), "f"(x), "f"(y) : "memory");
}
__device__ __forceinline__ void sts128(uint32_t a, uint4 v) {
    asm volatile("st.shared.v4.u32 [%0], {%1,%2,%3,%4};" ::"r"(a), "r"(v.x), "r"(v.y), "r"(v.z), "r"(v.w) : "memory");
}

constexpr uint32_t EMPTY = 0xffffffffu;
__device__ __forceinline__ void xld32(uint32_t& v, const uint32_t* p, uint32_t empty) {
    asm volatile("{\n.reg .pred p;\nsetp.eq.u32 p, %0, %2;\n@p ld.relaxed.gpu.global.u32 %0, [%1];\n}"
                 : "+r"(v) : "l"(p), "r"(empty) : "memory");
}
__device__ __forceinline__ void xld128(uint4& v, const uint32_t* p, uint32_t top) {
    asm volatile("{\n.reg .pred p;\nsetp.eq.u32 p, %5, 0xffffffff;\n@p ld.relaxed.gpu.global.v4.u32 {%0,%1,%2,%3}, [%4];\n}"
                 : "+r"(v.x), "+r"(v.y), "+r"(v.z), "+r"(v.w) : "l"(p), "r"(top) : "memory");
}
__device__ __forceinline__ void xst32(uint32_t* p, uint32_t v) {
    asm volatile("st.relaxed.gpu.global.u32 [%0], %1;" ::"l"(p), "r"(v) : "memory");
}
__device__ __forceinline__ void xst64(uint32_t* p, uint32_t a, uint32_t b) {
    asm volatile("st.relaxed.gpu.global.v2.u32 [%0], {%1,%2};" ::"l"(p), "r"(a), "r"(b) : "memory");
}
template <int N, int STRIDE>
__device__ __forceinline__ void poll128(uint4 (&v)[N], const uint32_t* src, uint32_t init) {
    uint32_t m[N];
#pragma unroll
    for (int i = 0; i < N; i++) {
        v[i] = make_uint4(init, init, init, init);
        m[i] = init;
    }
    int it = 0;
    bool again;
#pragma unroll 1
    do {
#pragma unroll
        for (int i = 0; i < N; i++) xld128(v[i], src + i * STRIDE, m[i]);
        uint32_t top = 0;
#pragma unroll
        for (int i = 0; i < N; i++) {
            m[i] = max(__vimax3_u32(v[i].x, v[i].y, v[i].z), v[i].w);
            top = max(top, m[i]);
        }
        again = __any_sync(0xffffffffu, top == EMPTY) && ++it < SPIN_LIMIT;
    } while (again);
}
__device__ __forceinline__ uint32_t poll32(const uint32_t* src, uint32_t init, uint32_t empty) {
    int it = 0;
    bool again;
#pragma unroll 1
    do {
        xld32(init, src, empty);
        again = __any_sync(0xffffffffu, init == empty) && ++it < SPIN_LIMIT;
    } while (again);
    return init;
}

__device__ __forceinline__ float bf_round(float v) { return __bfloat162float(__float2bfloat16_rn(v)); }
__device__ __forceinline__ uint32_t pack_bf(float lo, float hi) {
    uint32_t r;
    asm("cvt.rn.bf16x2.f32 %0, %1, %2;" : "=r"(r) : "f"(hi), "f"(lo));
    return r;
}
__device__ __forceinline__ float bf_lo(uint32_t w) { return __uint_as_float(w << 16); }
__device__ __forceinline__ float bf_hi(uint32_t w) { return __uint_as_float(w & 0xffff0000u); }

__device__ __forceinline__ void layernorm_row(const uint32_t (&w)[7], uint32_t dst, int lane) {
    const float shift = bf_lo(__shfl_sync(0xffffffffu, w[0], 0));
    float s = 0.f, ss = 0.f;
#pragma unroll
    for (int i = 0; i < 7; i++) {
        const float a = bf_lo(w[i]) - shift, b = bf_hi(w[i]) - shift;
        s += a + b;
        ss = fmaf(a, a, fmaf(b, b, ss));
    }
#pragma unroll
    for (int o = 16; o; o >>= 1) {
        s += __shfl_xor_sync(0xffffffffu, s, o);
        ss += __shfl_xor_sync(0xffffffffu, ss, o);
    }
    const float md = s * (1.f / DM);
    const float mean = bf_round(shift + md);
    const float var = bf_round(fmaxf(ss * (1.f / DM) - md * md, 0.f));
    float sd, inv;
    asm("sqrt.approx.f32 %0, %1;" : "=f"(sd) : "f"(bf_round(var + 1e-5f)));
    asm("rcp.approx.f32 %0, %1;" : "=f"(inv) : "f"(bf_round(sd)));
#pragma unroll
    for (int i = 0; i < 7; i++) {
        const float a = bf_round(bf_lo(w[i]) - mean) * inv, b = bf_round(bf_hi(w[i]) - mean) * inv;
        sts32(dst + (i * 32 + lane) * 4, pack_bf(a, b));
    }
}

template <int LD>
__device__ __forceinline__ void load_w448(uint32_t dst, const __nv_bfloat16* w, int ew, int lane, uint32_t on) {
    const int row = ew * 64 + (lane >> 2), ch = lane & 3;
    dst += row * 64 + ((ch ^ (lane >> 3)) << 4);
    w += row * LD + ch * 8;
    on = ew < 7 ? on : 0;
#pragma unroll
    for (int i = 0; i < 8; i++) cp16(dst + i * 512, w + i * 8 * LD, on);
}
__device__ __forceinline__ void frags_w448(uint32_t (&a)[8][4], uint32_t src, int ew, int lane) {
    const int r = lane & 7, mi = lane >> 3;
    const uint32_t base = src + ((ew < 7 ? ew : 0) * 64 + (mi >> 1) * 8 + r) * 64;
#pragma unroll
    for (int ks = 0; ks < 4; ks++)
#pragma unroll
        for (int mt = 0; mt < 2; mt++)
            ldsm4t(a[ks * 2 + mt], base + ks * 1024 + (((2 * mt + (mi & 1)) ^ (r >> 1)) << 4));
}
__device__ __forceinline__ float2 gemv448(const uint32_t (&a)[8][4], uint32_t sb, int ew, int lane, int et) {
    const int g = lane >> 2, t = lane & 3;
    bar_sync(2, 256);
    if (ew < 7) {
        float c[4][4] = {};
        const uint32_t xb = sb + SM_XN + (g * 228 + ew * 32 + t) * 4;
#pragma unroll
        for (int ks = 0; ks < 4; ks++) {
            const uint32_t b0 = lds32(xb + ks * 32), b1 = lds32(xb + ks * 32 + 16);
            mma(c[(ks & 1) * 2], a[ks * 2], b0, b1);
            mma(c[(ks & 1) * 2 + 1], a[ks * 2 + 1], b0, b1);
        }
        const uint32_t rb = sb + SM_RED + (ew * 288 + t * 72 + g) * 4;
#pragma unroll
        for (int mt = 0; mt < 2; mt++) {
            sts32f(rb + mt * 64, c[mt][0] + c[2 + mt][0]);
            sts32f(rb + mt * 64 + 144, c[mt][1] + c[2 + mt][1]);
            sts32f(rb + mt * 64 + 32, c[mt][2] + c[2 + mt][2]);
            sts32f(rb + mt * 64 + 176, c[mt][3] + c[2 + mt][3]);
        }
    }
    bar_sync(2, 256);
    float2 acc = make_float2(0.f, 0.f);
    if (et < 128) {
        const uint32_t rb = sb + SM_RED + ((et >> 4) * 36 + (et & 15) * 2) * 4;
#pragma unroll
        for (int w = 0; w < 7; w++) {
            const float2 v = lds64f(rb + w * 1152);
            acc.x += v.x;
            acc.y += v.y;
        }
    }
    return acc;
}

struct Params {
    const __nv_bfloat16 *x, *k, *v, *wq, *wo, *w1, *b1, *w2, *b2;
    __nv_bfloat16* out;
};

__global__ void __launch_bounds__(NTHREADS, 1) fused_decode_kernel(const Params p) {
    extern __shared__ __align__(1024) unsigned char smem[];
    const uint32_t sb = (uint32_t)__cvta_generic_to_shared(smem);
    const int tid = threadIdx.x, warp = tid >> 5, lane = tid & 31;
    const int c = blockIdx.x;
    const char* kbase = (const char*)p.k + (size_t)c * (SK * DH * 2);
    const char* vbase = (const char*)p.v + (size_t)c * (SK * DH * 2);

    Exchange* const gx = &g_x;

    if (warp == 4) {
        uint64_t pol = 0;
        if (lane == 0) {
            PROF_AT(true, 0);
            mbar_init(sb + BAR_FULL, 1);
            asm volatile("fence.mbarrier_init.release.cluster;" ::: "memory");
            asm volatile("createpolicy.fractional.L2::evict_first.b64 %0, 1.0;" : "=l"(pol));
            mbar_expect_tx(sb + BAR_FULL, CHUNK);
            bulk_load(sb + SM_RING, kbase, CHUNK, sb + BAR_FULL, pol);
#pragma unroll
            for (int s = 0; s < NS; s++) {
                if (s) mbar_init(sb + BAR_FULL + 8 * s, 1);
                mbar_init(sb + BAR_EMPTY + 8 * s, 4);
            }
            mbar_init(sb + BAR_DRY, 4);
            mbar_init(sb + BAR_TRIG, 4);
            mbar_init(sb + BAR_W0, 256);
            mbar_init(sb + BAR_W1, 4);
            mbar_init(sb + BAR_FREE0, 4);
            mbar_init(sb + BAR_WQ, 8);
            mbar_init(sb + BAR_WQIN, 8);
            asm volatile("fence.mbarrier_init.release.cluster;" ::: "memory");
        }
        __syncthreads();
        if (lane == 0) {
#pragma unroll 1
            for (int s = 1; s < NS; s++) {
                mbar_wait(s == 1 ? sb + BAR_WQIN : sb + BAR_FULL + 8 * (s - 2), 0);
                if (s == NS - 1) mbar_wait(sb + BAR_WQ, 0);
                mbar_expect_tx(sb + BAR_FULL + 8 * s, CHUNK);
                bulk_load(sb + SM_RING + s * CHUNK, kbase + s * CHUNK, CHUNK, sb + BAR_FULL + 8 * s, pol);
            }
            int s = 0;
            uint32_t ph = 0;
#pragma unroll 1
            for (int i = NS; i < 2 * NCH; i++) {
                const char* src = i < NCH ? kbase + (size_t)i * CHUNK : vbase + (size_t)(i - NCH) * CHUNK;
                mbar_wait(sb + BAR_EMPTY + 8 * s, ph);
                mbar_expect_tx(sb + BAR_FULL + 8 * s, CHUNK);
                bulk_load(sb + SM_RING + s * CHUNK, src, CHUNK, sb + BAR_FULL + 8 * s, pol);
                if (++s == NS) { s = 0; ph ^= 1; }
            }
        }
    } else if (warp < 4) {
        __syncthreads();
        const int g = lane >> 2, t = lane & 3, r = lane & 7, mi = lane >> 3;
        {
            bar_sync(3, 256);
            uint32_t* slot = gx->q + c * 128 + tid;
            const uint32_t w = poll32(slot, 0, 0);
            xst32(slot, 0);
            sts32(sb + SM_Q + tid * 4, ~w);
        }
        bar_sync(1, 128);
        PROF_AT(tid == 0, 2);
        int s = 0;
        uint32_t ph = 0;
        float rmax = -INFINITY;
        {
            uint32_t qf[32];
#pragma unroll
            for (int i = 0; i < 32; i++) qf[i] = lds32(sb + SM_Q + ((i ^ g) * 4 + t) * 4);
            uint32_t off[4];
#pragma unroll
            for (int i = 0; i < 4; i++)
                off[i] = sb + SM_RING + (warp * 16 + (mi & 1) * 8 + r) * 512 + (((2 * i + (mi >> 1)) ^ r) << 4);
            const bool owner = t == (g >> 1);
            uint32_t pdst = sb + SM_P + (t * 16 + warp * 4 + (g & 1)) * 2;
#pragma unroll 1
            for (int i = 0; i < NCH; i++) {
                mbar_wait(sb + BAR_FULL + 8 * s, ph);
                float acc[4][4] = {};
#pragma unroll
                for (int ks = 0; ks < 16; ks++) {
                    uint32_t a[4];
                    ldsm4(a, off[ks & 3] + s * CHUNK + (ks >> 2) * 128);
                    mma(acc[ks & 3], a, qf[2 * ks], qf[2 * ks + 1]);
                }
                __syncwarp();
                if (lane == 0) mbar_arrive(sb + BAR_EMPTY + 8 * s);
                float v[4];
#pragma unroll
                for (int e = 0; e < 4; e++) v[e] = (acc[0][e] + acc[1][e]) + (acc[2][e] + acc[3][e]);
                const float lo = (g & 1) ? v[1] : v[0], hi = (g & 1) ? v[3] : v[2];
                const uint32_t sc = pack_bf(bf_round(lo) * 0.0625f, bf_round(hi) * 0.0625f);
                if (owner) {
                    sts16(pdst, sc & 0xffffu);
                    sts16(pdst + 4, sc >> 16);
                    rmax = fmaxf(rmax, fmaxf(bf_lo(sc), bf_hi(sc)));
                }
                pdst += 128;
                if (++s == NS) { s = 0; ph ^= 1; }
            }
        }
        PROF_AT(tid == 0, 3);
        {
#pragma unroll
            for (int o = 16; o; o >>= 1) rmax = fmaxf(rmax, __shfl_xor_sync(0xffffffffu, rmax, o));
            if (lane == 0) sts32f(sb + SM_STAT + warp * 4, rmax);
            bar_sync(1, 128);
            const uint4 mx = lds128(sb + SM_STAT);
            const float m = fmaxf(fmaxf(__uint_as_float(mx.x), __uint_as_float(mx.y)),
                                  fmaxf(__uint_as_float(mx.z), __uint_as_float(mx.w)));
            float e[32];
            float sum = 0.f;
#pragma unroll
            for (int i = 0; i < 4; i++) {
                const uint4 w = lds128(sb + SM_P + (i * 128 + tid) * 16);
                const uint32_t ww[4] = {w.x, w.y, w.z, w.w};
#pragma unroll
                for (int j = 0; j < 4; j++) {
                    e[i * 8 + 2 * j] = __expf(bf_lo(ww[j]) - m);
                    e[i * 8 + 2 * j + 1] = __expf(bf_hi(ww[j]) - m);
                    sum += e[i * 8 + 2 * j] + e[i * 8 + 2 * j + 1];
                }
            }
#pragma unroll
            for (int o = 16; o; o >>= 1) sum += __shfl_xor_sync(0xffffffffu, sum, o);
            if (lane == 0) sts32f(sb + SM_STAT + 16 + warp * 4, sum);
            bar_sync(1, 128);
            const uint4 sm = lds128(sb + SM_STAT + 16);
            const float inv = 1.f / ((__uint_as_float(sm.x) + __uint_as_float(sm.y)) +
                                     (__uint_as_float(sm.z) + __uint_as_float(sm.w)));
#pragma unroll
            for (int i = 0; i < 4; i++) {
                uint4 w;
                w.x = pack_bf(e[i * 8 + 0] * inv, e[i * 8 + 1] * inv);
                w.y = pack_bf(e[i * 8 + 2] * inv, e[i * 8 + 3] * inv);
                w.z = pack_bf(e[i * 8 + 4] * inv, e[i * 8 + 5] * inv);
                w.w = pack_bf(e[i * 8 + 6] * inv, e[i * 8 + 7] * inv);
                sts128(sb + SM_P + (i * 128 + tid) * 16, w);
            }
            bar_sync(1, 128);
        }
        {
            uint32_t off[4];
#pragma unroll
            for (int i = 0; i < 4; i++)
                off[i] = sb + SM_RING + ((mi >> 1) * 8 + r) * 512 + warp * 128 + (((2 * i + (mi & 1)) ^ r) << 4);
            const uint32_t pmask = t == (g >> 1) ? ((g & 1) ? 0xffff0000u : 0x0000ffffu) : 0u;
            uint32_t* odst = gx->o + ((c & 15) * 8 + (c >> 4)) * 128 + (warp * 2 + (t >> 1)) * 16 + (g >> 1) * 4 +
                             (t & 1) * 2 + (g & 1);
#pragma unroll 1
            for (int pass = 0; pass < 2; pass++) {
                int n = pass * NCH;
                asm volatile("" : "+r"(n));
                float acc[4][4] = {};
                uint32_t psrc = sb + SM_P + t * 32;
#pragma unroll 1
                for (int i = 0; i < n; i++) {
                    const uint4 p0 = lds128(psrc), p1 = lds128(psrc + 16);
                    const uint32_t pb[8] = {p0.x & pmask, p0.y & pmask, p0.z & pmask, p0.w & pmask,
                                            p1.x & pmask, p1.y & pmask, p1.z & pmask, p1.w & pmask};
                    psrc += 128;
                    mbar_wait(sb + BAR_FULL + 8 * s, ph);
#pragma unroll
                    for (int ks = 0; ks < 4; ks++)
#pragma unroll
                        for (int T = 0; T < 4; T++) {
                            uint32_t a[4];
                            ldsm4t(a, off[T] + s * CHUNK + ks * 8192);
                            mma(acc[T], a, pb[2 * ks], pb[2 * ks + 1]);
                        }
                    __syncwarp();
                    if (lane == 0) {
                        mbar_arrive(sb + BAR_EMPTY + 8 * s);
                        if (i == DRY_AT) mbar_arrive(sb + BAR_DRY);
                        if (i == TRIG_AT) mbar_arrive(sb + BAR_TRIG);
                        if (i == FREE0_AT) mbar_arrive(sb + BAR_FREE0);
                    }
                    if (++s == NS) { s = 0; ph ^= 1; }
                }
                PROF_AT(tid == 0 && pass, 4);
                float ev[4], od[4];
#pragma unroll
                for (int T = 0; T < 4; T++) {
                    ev[T] = acc[T][0] + acc[T][3];
                    od[T] = acc[T][1] + acc[T][2];
                }
                ev[0] += __shfl_xor_sync(0xffffffffu, ev[1], 1);
                od[0] += __shfl_xor_sync(0xffffffffu, od[1], 1);
                ev[2] += __shfl_xor_sync(0xffffffffu, ev[3], 1);
                od[2] += __shfl_xor_sync(0xffffffffu, od[3], 1);
                ev[0] += __shfl_xor_sync(0xffffffffu, ev[2], 2);
                od[0] += __shfl_xor_sync(0xffffffffu, od[2], 2);
                const float other = __shfl_xor_sync(0xffffffffu, (g & 1) ? ev[0] : od[0], 4);
                const uint32_t w = (g & 1) ? pack_bf(other, od[0]) : pack_bf(ev[0], other);
                xst32(odst, n ? w : EMPTY);
                PROF_AT(tid == 0 && pass, 5);
                if (c < 112) {
                    bar_sync(1, 128);
                    if (n) mbar_wait(sb + BAR_W0, 0);
                    if (c < 56) {
                        const int row = tid >> 2, ch = tid & 3;
                        const uint32_t dst = sb + SM_WX + row * 64 + ((ch ^ ((row >> 1) & 3)) << 4);
                        const __nv_bfloat16* src = p.w1 + row * FF + c * 32 + ch * 8;
#pragma unroll
                        for (int i = 0; i < 14; i++) cp16(dst + i * 2048, src + i * 32 * FF, n);
                    } else {
                        const int row = tid >> 1, ch = tid & 1;
                        const uint32_t dst = sb + SM_WX + row * 32 + ((ch ^ ((row >> 2) & 1)) << 4);
                        const __nv_bfloat16* src = p.w2 + row * DM + ((c - 56) % 28) * 16 + ch * 8;
#pragma unroll
                        for (int i = 0; i < 28; i++) cp16(dst + i * 2048, src + i * 64 * DM, n);
                    }
                    cp_commit();
                    cp_wait<0>();
                    __syncwarp();
                    if (n && lane == 0) mbar_arrive(sb + BAR_W1);
                }
            }
        }
    } else {
        const int ew = warp - 5, et = tid - 160;
        const int g = lane >> 2, t = lane & 3, r = lane & 7, mi = lane >> 3;
        {
            load_w448<NH * DH>(sb + SM_WQ, p.wq + c * 32, ew, lane, 1);
            cp_commit();
            uint32_t w[7];
#pragma unroll
            for (int i = 0; i < 7; i++) w[i] = __ldg((const uint32_t*)p.x + ew * 224 + i * 32 + lane);
            __syncthreads();
            layernorm_row(w, sb + SM_XN + ew * 912, lane);
            cp_wait<0>();
            __syncwarp();
            if (lane == 0) mbar_arrive(sb + BAR_WQIN);
            uint32_t a[8][4];
            frags_w448(a, sb + SM_WQ, ew, lane);
            const float2 q = gemv448(a, sb, ew, lane, et);
            if (et < 128) {
                xst32(gx->q + ((et >> 4) * 16 + (c >> 3)) * 128 + (c & 7) * 16 + (et & 15), ~pack_bf(q.x, q.y));
                asm volatile("bar.arrive 3, 256;" ::: "memory");
            }
            PROF_AT(et == 0, 1);
            asm volatile("fence.proxy.async.shared::cta;" ::: "memory");
            __syncwarp();
            if (lane == 0) mbar_arrive(sb + BAR_WQ);
            PROF_AT(et == 0, 21);
        }
        const int hh = c / 7, jj = c - hh * 7;
        const int hb = (hh & 3) * 2 + (mi & 1);
        const bool is_f1 = c < 56;
        const int cg = (c - 56) % 28, half = (c - 56) / 28;
        uint32_t xres = 0, bias = 0;
        if (c < 112) {
            asm volatile("ld.global.nc.u32 %0, [%1];" : "=r"(xres) : "l"(p.x + hb * DM + jj * 64 + (hh >> 2) * 16 + r * 2));
            asm volatile("ld.global.nc.u32 %0, [%1];" : "=r"(bias)
                         : "l"(is_f1 ? p.b1 + c * 32 + (et & 15) * 2 : p.b2 + cg * 16 + r * 2));
        }
#pragma unroll 1
        for (int pass = 0; pass < 2; pass++) {
            uint32_t live = pass;
            asm volatile("" : "+r"(live));
            const uint32_t want = 0u - live, wipe = ~want;
            if (et == 0) {
                if (live) {
                    uint32_t seen;
                    asm volatile("atom.release.gpu.global.add.u32 %0, [%1], 1;" : "=r"(seen) : "l"(gx->count) : "memory");
                    PROF_AT(true, 20);
                    const uint32_t base = seen & ~(uint32_t)(NCTA - 1);
                    int it = 0;
                    for (seen++; c < 112 && seen - base < NCTA && ++it < SPIN_LIMIT;) {
                        __nanosleep(512);
                        asm volatile("ld.relaxed.gpu.global.u32 %0, [%1];" : "=r"(seen) : "l"(gx->count) : "memory");
                    }
                    asm volatile("ld.acquire.gpu.global.u32 %0, [%1];" : "=r"(seen) : "l"(gx->count) : "memory");
                    PROF_AT(true, 22);
                    mbar_wait(sb + BAR_TRIG, 0);
                    asm volatile("atom.relaxed.gpu.global.add.u32 %0, [%1], 1;" : "=r"(seen) : "l"(gx->count + 32) : "memory");
                    for (seen++; c < 112 && seen - base < TRIG_COUNT && ++it < SPIN_LIMIT;) {
                        __nanosleep(64);
                        asm volatile("ld.relaxed.gpu.global.u32 %0, [%1];" : "=r"(seen) : "l"(gx->count + 32) : "memory");
                    }
                    mbar_wait(sb + BAR_FREE0, 0);
                } else {
                    mbar_wait(sb + BAR_DRY, 0);
                }
            }
            __syncwarp();
            if (c >= 112) continue;
            bar_sync(2, 256);
            PROF_AT(et == 0, live ? 6 : 18);
            int lz = lane;
            asm volatile("" : "+r"(lz));
            {
                const int row = ew * 32 + (lz >> 3), ch = lz & 7;
                const uint32_t dst = sb + SM_WO + row * 128 + ((ch ^ (lz >> 3)) << 4);
                const __nv_bfloat16* src = p.wo + (hh * 256 + row) * DM + jj * 64 + ch * 8;
#pragma unroll
                for (int i = 0; i < 8; i++) cp16((dst ^ ((i & 1) << 6)) + i * 512, src + i * 4 * DM, live);
            }
            asm volatile("{\n.reg .pred p;\nsetp.ne.u32 p, %1, 0;\n@p cp.async.mbarrier.arrive.noinc.shared::cta.b64 [%0];\n}"
                         ::"r"(sb + BAR_W0), "r"(live) : "memory");
            {
                const uint32_t* osrc = gx->o + (hh * 8 + g) * 128 + ew * 16 + t * 4;
                uint4 o = make_uint4(want, want, want, want);
                uint32_t top = want;
                int it = 0;
#pragma unroll 1
                do {
                    xld128(o, osrc, top);
                    top = max(__vimax3_u32(o.x, o.y, o.z), o.w);
                } while (!mbar_test(sb + (live ? BAR_W0 : BAR_DRY), 0) && ++it < SPIN_LIMIT);
                PROF_AT(et == 0 && live, 7);
                const uint32_t base = sb + SM_WO + (ew * 32 + (mi >> 1) * 8 + r) * 128;
                const uint32_t wb = sb + SM_RED + (ew * 512 + lane * 2) * 4;
                uint32_t a[8][4];
#pragma unroll
                for (int mt = 0; mt < 4; mt++) {
                    ldsm4t(a[mt], base + (((2 * mt + (mi & 1)) ^ r) << 4));
                    ldsm4t(a[4 + mt], base + 2048 + (((2 * mt + (mi & 1)) ^ r) << 4));
                }
#pragma unroll 1
                do {
                    xld128(o, osrc, top);
                    top = max(__vimax3_u32(o.x, o.y, o.z), o.w);
                } while (__any_sync(0xffffffffu, top == EMPTY) && ++it < SPIN_LIMIT);
                PROF_AT(et == 0 && live, 8);
                float acc[4][4] = {};
#pragma unroll
                for (int mt = 0; mt < 4; mt++) mma(acc[mt], a[mt], o.x, o.y);
#pragma unroll
                for (int mt = 0; mt < 4; mt++) mma(acc[mt], a[4 + mt], o.z, o.w);
#pragma unroll
                for (int mt = 0; mt < 4; mt++) {
                    sts64f(wb + mt * 512, acc[mt][0], acc[mt][1]);
                    sts64f(wb + mt * 512 + 256, acc[mt][2], acc[mt][3]);
                }
                bar_sync(2, 256);
                float2 v[8];
#pragma unroll
                for (int w = 0; w < 8; w++) v[w] = lds64f(sb + SM_RED + (w * 512 + et * 2) * 4);
                const float s0 = ((v[0].x + v[1].x) + (v[2].x + v[3].x)) + ((v[4].x + v[5].x) + (v[6].x + v[7].x));
                const float s1 = ((v[0].y + v[1].y) + (v[2].y + v[3].y)) + ((v[4].y + v[5].y) + (v[6].y + v[7].y));
                xst64(gx->part + ((jj * 16 + (ew >> 1) * 4 + t) * 16 + hh) * 32 + ((ew & 1) * 8 + g) * 2,
                      __float_as_uint(s0) | wipe, __float_as_uint(s1) | wipe);
            }
            PROF_AT(et == 0 && live, 13);
            if (ew == 7) {
                uint4 v[4];
                poll128<4, 128>(v, gx->part + (jj * 16 + hh) * 512 + lane * 4, want);
                PROF_AT(lane == 0 && live, 14);
                const float f0 = (__uint_as_float(v[0].x) + __uint_as_float(v[1].x)) + (__uint_as_float(v[2].x) + __uint_as_float(v[3].x));
                const float f1 = (__uint_as_float(v[0].y) + __uint_as_float(v[1].y)) + (__uint_as_float(v[2].y) + __uint_as_float(v[3].y));
                const float f2 = (__uint_as_float(v[0].z) + __uint_as_float(v[1].z)) + (__uint_as_float(v[2].z) + __uint_as_float(v[3].z));
                const float f3 = (__uint_as_float(v[0].w) + __uint_as_float(v[1].w)) + (__uint_as_float(v[2].w) + __uint_as_float(v[3].w));
                const bool odd = mi & 1;
                float a0 = (odd ? f1 : f0) + __shfl_xor_sync(0xffffffffu, odd ? f0 : f1, 8);
                float a1 = (odd ? f3 : f2) + __shfl_xor_sync(0xffffffffu, odd ? f2 : f3, 8);
                a0 += __shfl_xor_sync(0xffffffffu, a0, 16);
                a1 += __shfl_xor_sync(0xffffffffu, a1, 16);
                const uint32_t at = pack_bf(a0, a1);
                const uint32_t hw = pack_bf(bf_lo(xres) + bf_lo(at), bf_hi(xres) + bf_hi(at));
                xst32(gx->h + (((mi >> 1) * 14 + jj * 2 + (hh >> 3)) * 8 + hb) * 16 + (r & 3) * 4 + ((hh >> 2) & 1) * 2 + (r >> 2),
                      hw | wipe);
                PROF_AT(lane == 0 && live, 9);
            }
            mbar_wait(sb + (live ? BAR_W1 : BAR_DRY), 0);
            PROF_AT(et == 32 && live, 15);
            if (is_f1) {
                constexpr uint32_t ONES = 0x3f803f80u;
                if (ew < 7) {
                    uint32_t a[8][4];
                    frags_w448(a, sb + SM_WX, ew, lane);
                    float cs[2][4] = {};
#pragma unroll
                    for (int ks = 0; ks < 4; ks++) {
                        mma(cs[0], a[ks * 2], ONES, ONES);
                        mma(cs[1], a[ks * 2 + 1], ONES, ONES);
                    }
                    if (t == 0) {
                        const uint32_t cb = sb + SM_XN + (ew * 32 + g) * 4;
                        sts32f(cb, cs[0][0]);
                        sts32f(cb + 32, cs[0][2]);
                        sts32f(cb + 64, cs[1][0]);
                        sts32f(cb + 96, cs[1][2]);
                    }
                    bar_sync(4, 224);
                    float2 colsum = make_float2(0.f, 0.f);
#pragma unroll
                    for (int w = 0; w < 7; w++) {
                        const float2 x = lds64f(sb + SM_XN + (w * 32 + (et & 15) * 2) * 4);
                        colsum.x += x.x;
                        colsum.y += x.y;
                    }
                    uint4 v[2];
                    poll128<2, 128>(v, gx->h + ((c & 1) * 14 + ew * 2) * 128 + lane * 4, want);
                    PROF_AT(et == 0 && live, 10);
                    float z[2][4] = {}, st[4] = {};
#pragma unroll
                    for (int ks = 0; ks < 4; ks++) {
                        const uint32_t b0 = (ks & 1) ? v[ks >> 1].z : v[ks >> 1].x, b1 = (ks & 1) ? v[ks >> 1].w : v[ks >> 1].y;
                        const uint32_t sa[4] = {b0, ONES, b1, ONES};
                        mma(st, sa, b0, b1);
                        mma(z[0], a[ks * 2], b0, b1);
                        mma(z[1], a[ks * 2 + 1], b0, b1);
                    }
                    const uint32_t wb = sb + SM_RED + 4096 + (ew * 288 + t * 72 + g) * 4;
                    if (t == (g >> 1))
                        sts64f(sb + SM_RED + 4096 + (ew * 288 + g * 36 + 32) * 4, (g & 1) ? st[3] : st[2], (g & 1) ? st[1] : st[0]);
#pragma unroll
                    for (int mt = 0; mt < 2; mt++) {
                        sts32f(wb + mt * 64, z[mt][0]);
                        sts32f(wb + mt * 64 + 144, z[mt][1]);
                        sts32f(wb + mt * 64 + 32, z[mt][2]);
                        sts32f(wb + mt * 64 + 176, z[mt][3]);
                    }
                    bar_sync(4, 224);
                    if (ew < 4) {
                        const int b = et >> 4, pr = et & 15;
                        const uint32_t rb = sb + SM_RED + 4096 + b * 144;
                        float2 sv[7], zv[7];
#pragma unroll
                        for (int w = 0; w < 7; w++) sv[w] = lds64f(rb + w * 1152 + 128);
#pragma unroll
                        for (int w = 0; w < 7; w++) zv[w] = lds64f(rb + w * 1152 + pr * 8);
                        const float mu = (((sv[0].x + sv[1].x) + (sv[2].x + sv[3].x)) + ((sv[4].x + sv[5].x) + sv[6].x)) * (1.f / DM);
                        const float sq = (((sv[0].y + sv[1].y) + (sv[2].y + sv[3].y)) + ((sv[4].y + sv[5].y) + sv[6].y)) * (1.f / DM);
                        const uint32_t mv = pack_bf(mu, fmaxf(fmaf(-mu, mu, sq), 0.f));
                        float sd, inv;
                        asm("sqrt.approx.f32 %0, %1;" : "=f"(sd) : "f"(bf_round(bf_hi(mv) + 1e-5f)));
                        asm("rcp.approx.f32 %0, %1;" : "=f"(inv) : "f"(bf_round(sd)));
                        const float z0 = ((zv[0].x + zv[1].x) + (zv[2].x + zv[3].x)) + ((zv[4].x + zv[5].x) + zv[6].x);
                        const float z1 = ((zv[0].y + zv[1].y) + (zv[2].y + zv[3].y)) + ((zv[4].y + zv[5].y) + zv[6].y);
                        const uint32_t u = pack_bf(fmaf(-bf_lo(mv), colsum.x, z0) * inv, fmaf(-bf_lo(mv), colsum.y, z1) * inv);
                        const uint32_t ub = pack_bf(bf_lo(u) + bf_lo(bias), bf_hi(u) + bf_hi(bias));
                        const float r0 = bf_lo(ub) > 0.f ? bf_lo(ub) : 0.f, r1 = bf_hi(ub) > 0.f ? bf_hi(ub) : 0.f;
                        xst32(gx->r + (((b >> 2) * 56 + c) * 4 + (b & 3)) * 16 + (pr & 3) * 4 + (pr >> 2),
                              pack_bf(r0 * r0, r1 * r1) | wipe);
                    }
                    PROF_AT(et == 0 && live, 11);
                }
            } else {
                uint32_t a[14][4];
                const uint32_t base = sb + SM_WX + (ew * 224 + (mi >> 1) * 8 + r) * 32 + (((mi & 1) ^ (r >> 2)) << 4);
#pragma unroll
                for (int ks = 0; ks < 14; ks++) ldsm4t(a[ks], base + ks * 512);
                const uint32_t hres = poll32(gx->h + (((c & 1) * 14 + (cg >> 1)) * 8 + half * 4 + mi) * 16 + (r & 3) * 4 +
                                             (cg & 1) * 2 + (r >> 2), want, EMPTY);
                PROF_AT(et == 0 && live, 16);
                uint4 v[7];
                poll128<7, 64>(v, gx->r + (half * 56 + ew * 7) * 64 + (lane & 15) * 4, lane < 16 ? want : 0u);
                PROF_AT(et == 0 && live, 17);
                float acc[4][4] = {};
#pragma unroll
                for (int i = 0; i < 7; i++) {
                    mma(acc[(2 * i) & 3], a[2 * i], v[i].x, v[i].y);
                    mma(acc[(2 * i + 1) & 3], a[2 * i + 1], v[i].z, v[i].w);
                }
                if (t < 2) {
                    const uint32_t wb = sb + SM_XN + (ew * 80 + t * 40 + g) * 4;
                    sts32f(wb, (acc[0][0] + acc[1][0]) + (acc[2][0] + acc[3][0]));
                    sts32f(wb + 80, (acc[0][1] + acc[1][1]) + (acc[2][1] + acc[3][1]));
                    sts32f(wb + 32, (acc[0][2] + acc[1][2]) + (acc[2][2] + acc[3][2]));
                    sts32f(wb + 112, (acc[0][3] + acc[1][3]) + (acc[2][3] + acc[3][3]));
                }
                bar_sync(2, 256);
                if (ew == 0) {
                    float2 x[8];
#pragma unroll
                    for (int w = 0; w < 8; w++) x[w] = lds64f(sb + SM_XN + (w * 80 + mi * 20 + r * 2) * 4);
                    const float s0 = ((x[0].x + x[1].x) + (x[2].x + x[3].x)) + ((x[4].x + x[5].x) + (x[6].x + x[7].x));
                    const float s1 = ((x[0].y + x[1].y) + (x[2].y + x[3].y)) + ((x[4].y + x[5].y) + (x[6].y + x[7].y));
                    const uint32_t y = pack_bf(s0, s1);
                    const uint32_t yb = pack_bf(bf_lo(y) + bf_lo(bias), bf_hi(y) + bf_hi(bias));
                    uint32_t res = pack_bf(bf_lo(hres) + bf_lo(yb), bf_hi(hres) + bf_hi(yb));
                    asm volatile("" : "+r"(res));
                    if (live) ((uint32_t*)p.out)[(half * 4 + mi) * 224 + cg * 8 + r] = res;
                    PROF_AT(et == 0 && live, 12);
                }
            }
            if (!live) bar_sync(2, 256);
            PROF_AT(et == 0 && !live, 19);
        }
    }
}

}

extern "C" void kernel_launch(void* const* d_in, const int* in_sizes, int n_in, void* d_out, int out_size) {
    (void)in_sizes; (void)n_in; (void)out_size;
    Params p;
    p.x = (const __nv_bfloat16*)d_in[0];
    p.k = (const __nv_bfloat16*)d_in[1];
    p.v = (const __nv_bfloat16*)d_in[2];
    p.wq = (const __nv_bfloat16*)d_in[3];
    p.wo = (const __nv_bfloat16*)d_in[4];
    p.w1 = (const __nv_bfloat16*)d_in[6];
    p.b1 = (const __nv_bfloat16*)d_in[7];
    p.w2 = (const __nv_bfloat16*)d_in[8];
    p.b2 = (const __nv_bfloat16*)d_in[9];
    p.out = (__nv_bfloat16*)d_out;
    cudaFuncSetAttribute(fused_decode_kernel, cudaFuncAttributeMaxDynamicSharedMemorySize, SM_TOTAL);
    fused_decode_kernel<<<NCTA, NTHREADS, SM_TOTAL>>>(p);
}
```

```cpp
#include <cuda_runtime.h>
#include <cuda_bf16.h>
#include <stdint.h>

namespace {

constexpr int DM = 448, NH = 16, SK = 4096, DH = 256, FF = 1792;
constexpr int NCTA = 128;
constexpr int CHUNK = 32768;
constexpr int NCH = SK / 64;
constexpr int NS = 5;
constexpr int HEAD_BYTES = 8192;
constexpr int ALL_CHUNKS = NCTA * 2 * NCH;
#define TRIG_LEFT 200
#define LIFT_LEFT 300
#define LEAD1 256
#define LEAD2 -128
#define MON_SLEEP 200
#define W1_GATE BAR_W0
#define W2_GATE BAR_E1
#define PF_MODE 0
#define H_SLEEP 0
#define R_SLEEP 0
constexpr int NTHREADS = 13 * 32;
constexpr int SPIN_LIMIT = 1 << 20;

constexpr int SM_RING = 0;
constexpr int SM_WX = 0;
constexpr int SM_WQ = NS * CHUNK;
constexpr int SM_WO = SM_WQ;
constexpr int SM_P = SM_WQ + 32768;
constexpr int SM_RED = SM_P + 8192;
constexpr int SM_XN = SM_RED + 8 * 544 * 4;
constexpr int SM_Q = SM_XN + 8 * 456 * 2;
constexpr int SM_STAT = SM_Q + 512;
constexpr int SM_PROG = SM_STAT + 32, SM_DEPTH = SM_STAT + 36;
constexpr int SM_BAR = SM_STAT + 64;
constexpr int BAR_FULL = SM_BAR, BAR_EMPTY = BAR_FULL + 8 * NS, BAR_WO = BAR_EMPTY + 8 * NS, BAR_DRY = BAR_WO + 64,
              BAR_WQ = BAR_DRY + 8, BAR_Q = BAR_WQ + 8, BAR_W0 = BAR_Q + 8, BAR_E1 = BAR_W0 + 8, BAR_W1 = BAR_E1 + 8;
constexpr int SM_TOTAL = BAR_W1 + 8;
static_assert(SM_TOTAL <= 232448, "shared memory budget");

struct Exchange {
    uint32_t q[NCTA * 128];
    uint32_t o[NH * 8 * 128];
    uint32_t part[14 * 8 * 16 * 32];
    uint32_t h[2 * 14 * 8 * 16];
    uint32_t r[2 * 56 * 4 * 16];
    uint32_t count[64];
    uint32_t sink[8 * 224];
};
__device__ __align__(128) Exchange g_x;

#define PROF_AT(cond, slot) do { } while (0)
#define PROF_CHUNK(i) do { } while (0)

__device__ __forceinline__ void mbar_init(uint32_t bar, uint32_t count) {
    asm volatile("mbarrier.init.shared::cta.b64 [%0], %1;" ::"r"(bar), "r"(count) : "memory");
}
__device__ __forceinline__ void mbar_arrive(uint32_t bar) {
    asm volatile("mbarrier.arrive.shared::cta.b64 _, [%0];" ::"r"(bar) : "memory");
}
__device__ __forceinline__ void mbar_expect_tx(uint32_t bar, uint32_t bytes) {
    asm volatile("mbarrier.arrive.expect_tx.shared::cta.b64 _, [%0], %1;" ::"r"(bar), "r"(bytes) : "memory");
}
__device__ __forceinline__ void mbar_wait(uint32_t bar, uint32_t parity) {
    uint32_t done;
    int it = 0;
    do {
        asm volatile("{\n.reg .pred p;\nmbarrier.try_wait.parity.shared::cta.b64 p, [%1], %2;\nselp.u32 %0, 1, 0, p;\n}"
                     : "=r"(done) : "r"(bar), "r"(parity) : "memory");
    } while (!done && ++it < SPIN_LIMIT);
}
__device__ __forceinline__ uint32_t mbar_test(uint32_t bar, uint32_t parity) {
    uint32_t done;
    asm volatile("{\n.reg .pred p;\nmbarrier.test_wait.parity.shared::cta.b64 p, [%1], %2;\nselp.u32 %0, 1, 0, p;\n}"
                 : "=r"(done) : "r"(bar), "r"(parity) : "memory");
    return done;
}
__device__ __forceinline__ void bulk_load(uint32_t dst, const void* src, uint32_t bytes, uint32_t bar, uint64_t pol) {
    asm volatile("cp.async.bulk.shared::cluster.global.mbarrier::complete_tx::bytes.L2::cache_hint [%0], [%1], %2, [%3], %4;"
                 ::"r"(dst), "l"(src), "r"(bytes), "r"(bar), "l"(pol) : "memory");
}
__device__ __forceinline__ void cp16(uint32_t dst, const void* src, uint32_t on) {
    asm volatile("{\n.reg .pred p;\nsetp.ne.u32 p, %2, 0;\n@p cp.async.cg.shared.global [%0], [%1], 16;\n}"
                 ::"r"(dst), "l"(src), "r"(on) : "memory");
}
__device__ __forceinline__ void cp_commit() { asm volatile("cp.async.commit_group;" ::: "memory"); }
template <int N> __device__ __forceinline__ void cp_wait() { asm volatile("cp.async.wait_group %0;" ::"n"(N) : "memory"); }
__device__ __forceinline__ void bar_sync(int id, int n) { asm volatile("bar.sync %0, %1;" ::"r"(id), "r"(n) : "memory"); }

__device__ __forceinline__ void ldsm4(uint32_t (&r)[4], uint32_t a) {
    asm volatile("ldmatrix.sync.aligned.m8n8.x4.shared.b16 {%0,%1,%2,%3}, [%4];"
                 : "=r"(r[0]), "=r"(r[1]), "=r"(r[2]), "=r"(r[3]) : "r"(a) : "memory");
}
__device__ __forceinline__ void ldsm4t(uint32_t (&r)[4], uint32_t a) {
    asm volatile("ldmatrix.sync.aligned.m8n8.x4.trans.shared.b16 {%0,%1,%2,%3}, [%4];"
                 : "=r"(r[0]), "=r"(r[1]), "=r"(r[2]), "=r"(r[3]) : "r"(a) : "memory");
}
__device__ __forceinline__ void mma(float (&c)[4], const uint32_t (&a)[4], uint32_t b0, uint32_t b1) {
    asm volatile("mma.sync.aligned.m16n8k16.row.col.f32.bf16.bf16.f32 {%0,%1,%2,%3}, {%4,%5,%6,%7}, {%8,%9}, {%0,%1,%2,%3};"
                 : "+f"(c[0]), "+f"(c[1]), "+f"(c[2]), "+f"(c[3])
                 : "r"(a[0]), "r"(a[1]), "r"(a[2]), "r"(a[3]), "r"(b0), "r"(b1));
}
__device__ __forceinline__ void mma0(float (&c)[4], const uint32_t (&a)[4], uint32_t b0, uint32_t b1) {
    asm volatile("mma.sync.aligned.m16n8k16.row.col.f32.bf16.bf16.f32 {%0,%1,%2,%3}, {%4,%5,%6,%7}, {%8,%9}, {%10,%10,%10,%10};"
                 : "=f"(c[0]), "=f"(c[1]), "=f"(c[2]), "=f"(c[3])
                 : "r"(a[0]), "r"(a[1]), "r"(a[2]), "r"(a[3]), "r"(b0), "r"(b1), "f"(0.f));
}
__device__ __forceinline__ uint32_t lds32(uint32_t a) {
    uint32_t v;
    asm volatile("ld.shared.u32 %0, [%1];" : "=r"(v) : "r"(a) : "memory");
    return v;
}
__device__ __forceinline__ float2 lds64f(uint32_t a) {
    float2 v;
    asm volatile("ld.shared.v2.f32 {%0,%1}, [%2];" : "=f"(v.x), "=f"(v.y) : "r"(a) : "memory");
    return v;
}
__device__ __forceinline__ uint4 lds128(uint32_t a) {
    uint4 v;
    asm volatile("ld.shared.v4.u32 {%0,%1,%2,%3}, [%4];" : "=r"(v.x), "=r"(v.y), "=r"(v.z), "=r"(v.w) : "r"(a) : "memory");
    return v;
}
__device__ __forceinline__ void sts16(uint32_t a, uint32_t v) {
    asm volatile("st.shared.u16 [%0], %1;" ::"r"(a), "h"((unsigned short)v) : "memory");
}
__device__ __forceinline__ void sts32(uint32_t a, uint32_t v) {
    asm volatile("st.shared.u32 [%0], %1;" ::"r"(a), "r"(v) : "memory");
}
__device__ __forceinline__ void sts32f(uint32_t a, float v) {
    asm volatile("st.shared.f32 [%0], %1;" ::"r"(a), "f"(v) : "memory");
}
__device__ __forceinline__ void sts64f(uint32_t a, float x, float y) {
    asm volatile("st.shared.v2.f32 [%0], {%1,%2};" ::"r"(a), "f"(x), "f"(y) : "memory");
}
__device__ __forceinline__ void sts128(uint32_t a, uint4 v) {
    asm volatile("st.shared.v4.u32 [%0], {%1,%2,%3,%4};" ::"r"(a), "r"(v.x), "r"(v.y), "r"(v.z), "r"(v.w) : "memory");
}

constexpr uint32_t EMPTY = 0xffffffffu;
__device__ __forceinline__ void xld32(uint32_t& v, const uint32_t* p, uint32_t empty) {
    asm volatile("{\n.reg .pred p;\nsetp.eq.u32 p, %0, %2;\n@p ld.relaxed.gpu.global.u32 %0, [%1];\n}"
                 : "+r"(v) : "l"(p), "r"(empty) : "memory");
}
__device__ __forceinline__ void xld128(uint4& v, const uint32_t* p, uint32_t top) {
    asm volatile("{\n.reg .pred p;\nsetp.eq.u32 p, %5, 0xffffffff;\n@p ld.relaxed.gpu.global.v4.u32 {%0,%1,%2,%3}, [%4];\n}"
                 : "+r"(v.x), "+r"(v.y), "+r"(v.z), "+r"(v.w) : "l"(p), "r"(top) : "memory");
}
__device__ __forceinline__ void xst32(uint32_t* p, uint32_t v) {
    asm volatile("st.relaxed.gpu.global.u32 [%0], %1;" ::"l"(p), "r"(v) : "memory");
}
__device__ __forceinline__ void xst64(uint32_t* p, uint32_t a, uint32_t b) {
    asm volatile("st.relaxed.gpu.global.v2.u32 [%0], {%1,%2};" ::"l"(p), "r"(a), "r"(b) : "memory");
}
__device__ __forceinline__ uint32_t top_word(const uint4& v) { return max(__vimax3_u32(v.x, v.y, v.z), v.w); }
template <int N, int STRIDE, class F>
__device__ __forceinline__ void poll128(const uint32_t* src, uint32_t init, uint32_t init_last, F use) {
    uint4 v[N];
    uint32_t m[N];
#pragma unroll
    for (int i = 0; i < N; i++) {
        m[i] = i == N - 1 ? init_last : init;
        v[i] = make_uint4(m[i], m[i], m[i], m[i]);
    }
    int left = SPIN_LIMIT;
    bool again;
#pragma unroll 1
    do {
#pragma unroll
        for (int i = 0; i < N; i++) xld128(v[i], src + i * STRIDE, m[i]);
        left--;
        uint32_t top = 0;
#pragma unroll
        for (int i = 0; i < N; i++) {
            m[i] = top_word(v[i]);
            top = max(top, m[i]);
        }
        again = __any_sync(0xffffffffu, top == EMPTY && left > 0);
        use(v);
    } while (again);
}
__device__ __forceinline__ uint32_t poll32(const uint32_t* src, uint32_t init, uint32_t empty) {
    int left = SPIN_LIMIT;
#pragma unroll 1
    do {
        xld32(init, src, empty);
        left--;
    } while (__any_sync(0xffffffffu, init == empty && left > 0));
    return init;
}
__device__ __forceinline__ uint32_t pin(uint32_t v) {
    asm volatile("shfl.sync.bfly.b32 %0, %0, 0, 0x1f, 0xffffffff;" : "+r"(v));
    return v;
}
__device__ __forceinline__ uint32_t bf2_add(uint32_t a, uint32_t b) {
    uint32_t r;
    asm("add.rn.bf16x2 %0, %1, %2;" : "=r"(r) : "r"(a), "r"(b));
    return r;
}
__device__ __forceinline__ uint32_t bf2_relu_sq(uint32_t a) {
    uint32_t r;
    asm("{\n.reg .b32 m;\nmax.bf16x2 m, %1, %2;\nmul.rn.bf16x2 %0, m, m;\n}" : "=r"(r) : "r"(a), "r"(0));
    return r;
}

__device__ __forceinline__ uint32_t pack_bf(float lo, float hi) {
    uint32_t r;
    asm("cvt.rn.bf16x2.f32 %0, %1, %2;" : "=r"(r) : "f"(hi), "f"(lo));
    return r;
}
__device__ __forceinline__ float bf_round(float v) { return __uint_as_float(pack_bf(0.f, v)); }
__device__ __forceinline__ float bf_lo(uint32_t w) { return __uint_as_float(w << 16); }
__device__ __forceinline__ float bf_hi(uint32_t w) { return __uint_as_float(w & 0xffff0000u); }

__device__ __forceinline__ float inv_std(float var) {
    float sd, inv;
    asm("sqrt.approx.ftz.f32 %0, %1;" : "=f"(sd) : "f"(bf_round(var + 1e-5f)));
    asm("rcp.approx.ftz.f32 %0, %1;" : "=f"(inv) : "f"(bf_round(sd)));
    return inv;
}

__device__ __forceinline__ void layernorm_row(const uint32_t (&w)[7], uint32_t dst, int lane) {
    const float shift = bf_lo(__shfl_sync(0xffffffffu, w[0], 0));
    float s = 0.f, ss = 0.f;
#pragma unroll
    for (int i = 0; i < 7; i++) {
        const float a = bf_lo(w[i]) - shift, b = bf_hi(w[i]) - shift;
        s += a + b;
        ss = fmaf(a, a, fmaf(b, b, ss));
    }
#pragma unroll
    for (int o = 16; o; o >>= 1) {
        s += __shfl_xor_sync(0xffffffffu, s, o);
        ss += __shfl_xor_sync(0xffffffffu, ss, o);
    }
    const float md = s * (1.f / DM);
    const float mean = bf_round(shift + md);
    const float inv = inv_std(bf_round(fmaxf(ss * (1.f / DM) - md * md, 0.f)));
#pragma unroll
    for (int i = 0; i < 7; i++) {
        const float a = bf_round(bf_lo(w[i]) - mean) * inv, b = bf_round(bf_hi(w[i]) - mean) * inv;
        sts32(dst + (i * 32 + lane) * 4, pack_bf(a, b));
    }
}

__device__ __forceinline__ void frags_w448(uint32_t (&a)[8][4], uint32_t src, int ew, int lane) {
    const int r = lane & 7, mi = lane >> 3;
    const uint32_t base = src + ((ew < 7 ? ew : 0) * 64 + (mi >> 1) * 8 + r) * 64;
#pragma unroll
    for (int ks = 0; ks < 4; ks++)
#pragma unroll
        for (int mt = 0; mt < 2; mt++)
            ldsm4t(a[ks * 2 + mt], base + ks * 1024 + (((2 * mt + (mi & 1)) ^ (r >> 1)) << 4));
}
__device__ __forceinline__ float2 gemv448(const uint32_t (&a)[8][4], uint32_t sb, int ew, int lane, int et) {
    const int g = lane >> 2, t = lane & 3;
    bar_sync(2, 256);
    if (ew < 7) {
        float c[4][4] = {};
        const uint32_t xb = sb + SM_XN + (g * 228 + ew * 32 + t) * 4;
#pragma unroll
        for (int ks = 0; ks < 4; ks++) {
            const uint32_t b0 = lds32(xb + ks * 32), b1 = lds32(xb + ks * 32 + 16);
            mma(c[(ks & 1) * 2], a[ks * 2], b0, b1);
            mma(c[(ks & 1) * 2 + 1], a[ks * 2 + 1], b0, b1);
        }
        const uint32_t rb = sb + SM_RED + (ew * 288 + t * 72 + g) * 4;
#pragma unroll
        for (int mt = 0; mt < 2; mt++) {
            sts32f(rb + mt * 64, c[mt][0] + c[2 + mt][0]);
            sts32f(rb + mt * 64 + 144, c[mt][1] + c[2 + mt][1]);
            sts32f(rb + mt * 64 + 32, c[mt][2] + c[2 + mt][2]);
            sts32f(rb + mt * 64 + 176, c[mt][3] + c[2 + mt][3]);
        }
    }
    bar_sync(2, 256);
    float2 acc = make_float2(0.f, 0.f);
    if (et < 128) {
        const uint32_t rb = sb + SM_RED + ((et >> 4) * 36 + (et & 15) * 2) * 4;
#pragma unroll
        for (int w = 0; w < 7; w++) {
            const float2 v = lds64f(rb + w * 1152);
            acc.x += v.x;
            acc.y += v.y;
        }
    }
    return acc;
}

struct Params {
    const __nv_bfloat16 *x, *k, *v, *wq, *wo, *w1, *b1, *w2, *b2;
    __nv_bfloat16* out;
    Exchange* xch;
};

__global__ void __launch_bounds__(NTHREADS, 1) fused_decode_kernel(const Params p) {
    extern __shared__ __align__(1024) unsigned char smem[];
    const uint32_t sb = (uint32_t)__cvta_generic_to_shared(smem);
    const int tid = threadIdx.x, warp = tid >> 5, lane = tid & 31;
    const int c = blockIdx.x;
    const char* kbase = (const char*)p.k + (size_t)c * (SK * DH * 2);
    const char* vbase = (const char*)p.v + (size_t)c * (SK * DH * 2);

    Exchange* const gx = p.xch;

    if (warp == 4) {
        uint64_t pol = 0;
        if (lane == 0) {
            PROF_AT(true, 0);
            mbar_init(sb + BAR_FULL, 1);
            asm volatile("fence.mbarrier_init.release.cluster;" ::: "memory");
            asm volatile("createpolicy.fractional.L2::evict_first.b64 %0, 1.0;" : "=l"(pol));
            mbar_expect_tx(sb + BAR_FULL, CHUNK);
            bulk_load(sb + SM_RING, kbase, HEAD_BYTES, sb + BAR_FULL, pol);
            PROF_AT(true, 28);
#pragma unroll
            for (int s = 0; s < NS; s++) {
                if (s) mbar_init(sb + BAR_FULL + 8 * s, 1);
                mbar_init(sb + BAR_EMPTY + 8 * s, 4);
            }
#pragma unroll
            for (int w = 0; w < 8; w++) mbar_init(sb + BAR_WO + 8 * w, 32);
            mbar_init(sb + BAR_DRY, 4);
            mbar_init(sb + BAR_WQ, 128);
            mbar_init(sb + BAR_Q, 1);
            mbar_init(sb + BAR_W0, 256);
            mbar_init(sb + BAR_E1, 1);
            mbar_init(sb + BAR_W1, 4);
            sts32(sb + SM_PROG, 0);
            sts32(sb + SM_DEPTH, 2);
            asm volatile("fence.mbarrier_init.release.cluster;" ::: "memory");
        }
        __syncthreads();
        if (lane == 0) {
            bulk_load(sb + SM_RING + HEAD_BYTES, kbase + HEAD_BYTES, CHUNK - HEAD_BYTES, sb + BAR_FULL, pol);
            mbar_wait(sb + BAR_WQ, 0);
            int s = 1, sl = 0, landed = 0;
            uint32_t ph = 1, phl = 0;
#pragma unroll 1
            for (int i = 1; i <= 2 * NCH; i++) {
                const char* src = i < NCH ? kbase + (size_t)i * CHUNK : vbase + (size_t)(i - NCH) * CHUNK;
                for (int it = 0; landed < (i < 2 * NCH ? i + 1 - (int)lds32(sb + SM_DEPTH) : i); it++) {
                    if (mbar_test(sb + BAR_FULL + 8 * sl, phl) || it >= 16 * SPIN_LIMIT) {
                        PROF_AT(landed == 0, 29);
                        asm volatile("red.relaxed.gpu.global.add.u32 [%0], 1;" ::"l"(gx->count + 32) : "memory");
                        sts32(sb + SM_PROG, ++landed);
                        if (++sl == NS) { sl = 0; phl ^= 1; }
                    } else {
                        __nanosleep(20);
                    }
                }
                if (i == 2 * NCH) break;
                mbar_wait(sb + BAR_EMPTY + 8 * s, ph);
                mbar_expect_tx(sb + BAR_FULL + 8 * s, CHUNK);
                bulk_load(sb + SM_RING + s * CHUNK, src, CHUNK, sb + BAR_FULL + 8 * s, pol);
                if (++s == NS) { s = 0; ph ^= 1; }
            }
        }
    } else if (warp < 4) {
        const int g = lane >> 2, t = lane & 3, r = lane & 7, mi = lane >> 3;
        {
            uint32_t* slot = gx->q + c * 128 + tid;
            uint32_t w = 0;
            xld32(w, slot, 0);
            const int row = tid >> 2, ch = tid & 3;
            const uint32_t dst = sb + SM_WQ + row * 64 + ((ch ^ ((row >> 1) & 3)) << 4);
            const __nv_bfloat16* src = p.wq + row * (NH * DH) + c * 32 + ch * 8;
#pragma unroll
            for (int i = 0; i < 14; i++)
                asm volatile("cp.async.cg.shared.global [%0], [%1], 16;" ::"r"(dst + i * 2048), "l"(src + i * 32 * (NH * DH)) : "memory");
            PROF_AT(tid == 0, 23);
            __syncthreads();
            asm volatile("cp.async.mbarrier.arrive.noinc.shared::cta.b64 [%0];" ::"r"(sb + BAR_WQ) : "memory");
            bar_sync(3, 256);
            w = poll32(slot, w, 0);
            xst32(slot, 0);
            sts32(sb + SM_Q + tid * 4, ~w);
        }
        bar_sync(1, 128);
        if (tid == 0) mbar_arrive(sb + BAR_Q);
        PROF_AT(tid == 0, 2);
        int s = 0;
        uint32_t ph = 0;
        float rmax = -INFINITY;
        {
            uint32_t qf[32];
#pragma unroll
            for (int i = 0; i < 32; i++) qf[i] = lds32(sb + SM_Q + ((i ^ g) * 4 + t) * 4);
            uint32_t off[4];
#pragma unroll
            for (int i = 0; i < 4; i++)
                off[i] = sb + SM_RING + (warp * 16 + (mi & 1) * 8 + r) * 512 + (((2 * i + (mi >> 1)) ^ r) << 4);
            const bool owner = t == (g >> 1);
            uint32_t pdst = sb + SM_P + (t * 16 + warp * 4 + (g & 1)) * 2;
#pragma unroll 1
            for (int i = 0; i < NCH; i++) {
                mbar_wait(sb + BAR_FULL + 8 * s, ph);
                PROF_CHUNK(i);
                float acc[4][4] = {};
#pragma unroll
                for (int ks = 0; ks < 16; ks++) {
                    uint32_t a[4];
                    ldsm4(a, off[ks & 3] + s * CHUNK + (ks >> 2) * 128);
                    mma(acc[ks & 3], a, qf[2 * ks], qf[2 * ks + 1]);
                }
                __syncwarp();
                if (lane == 0) mbar_arrive(sb + BAR_EMPTY + 8 * s);
                float v[4];
#pragma unroll
                for (int e = 0; e < 4; e++) v[e] = (acc[0][e] + acc[1][e]) + (acc[2][e] + acc[3][e]);
                const float lo = (g & 1) ? v[1] : v[0], hi = (g & 1) ? v[3] : v[2];
                const uint32_t sc = pack_bf(bf_round(lo) * 0.0625f, bf_round(hi) * 0.0625f);
                if (owner) {
                    sts16(pdst, sc & 0xffffu);
                    sts16(pdst + 4, sc >> 16);
                    rmax = fmaxf(rmax, fmaxf(bf_lo(sc), bf_hi(sc)));
                }
                pdst += 128;
                if (++s == NS) { s = 0; ph ^= 1; }
            }
        }
        PROF_AT(tid == 0, 3);
        {
#pragma unroll
            for (int o = 16; o; o >>= 1) rmax = fmaxf(rmax, __shfl_xor_sync(0xffffffffu, rmax, o));
            if (lane == 0) sts32f(sb + SM_STAT + warp * 4, rmax);
            bar_sync(1, 128);
            const uint4 mx = lds128(sb + SM_STAT);
            const float m = fmaxf(fmaxf(__uint_as_float(mx.x), __uint_as_float(mx.y)),
                                  fmaxf(__uint_as_float(mx.z), __uint_as_float(mx.w)));
            float e[32];
            float sum = 0.f;
#pragma unroll
            for (int i = 0; i < 4; i++) {
                const uint4 w = lds128(sb + SM_P + (i * 128 + tid) * 16);
                const uint32_t ww[4] = {w.x, w.y, w.z, w.w};
#pragma unroll
                for (int j = 0; j < 4; j++) {
                    e[i * 8 + 2 * j] = __expf(bf_lo(ww[j]) - m);
                    e[i * 8 + 2 * j + 1] = __expf(bf_hi(ww[j]) - m);
                    sum += e[i * 8 + 2 * j] + e[i * 8 + 2 * j + 1];
                }
            }
#pragma unroll
            for (int o = 16; o; o >>= 1) sum += __shfl_xor_sync(0xffffffffu, sum, o);
            if (lane == 0) sts32f(sb + SM_STAT + 16 + warp * 4, sum);
            bar_sync(1, 128);
            const uint4 sm = lds128(sb + SM_STAT + 16);
            const float inv = 1.f / ((__uint_as_float(sm.x) + __uint_as_float(sm.y)) +
                                     (__uint_as_float(sm.z) + __uint_as_float(sm.w)));
#pragma unroll
            for (int i = 0; i < 4; i++) {
                uint4 w;
                w.x = pack_bf(e[i * 8 + 0] * inv, e[i * 8 + 1] * inv);
                w.y = pack_bf(e[i * 8 + 2] * inv, e[i * 8 + 3] * inv);
                w.z = pack_bf(e[i * 8 + 4] * inv, e[i * 8 + 5] * inv);
                w.w = pack_bf(e[i * 8 + 6] * inv, e[i * 8 + 7] * inv);
                sts128(sb + SM_P + (i * 128 + tid) * 16, w);
            }
            bar_sync(1, 128);
        }
        {
            uint32_t off[4];
#pragma unroll
            for (int i = 0; i < 4; i++)
                off[i] = sb + SM_RING + ((mi >> 1) * 8 + r) * 512 + warp * 128 + (((2 * i + (mi & 1)) ^ r) << 4);
            const uint32_t pmask = t == (g >> 1) ? ((g & 1) ? 0xffff0000u : 0x0000ffffu) : 0u;
            uint32_t* odst = gx->o + ((c & 15) * 8 + (c >> 4)) * 128 + (warp * 2 + (t >> 1)) * 16 + (g >> 1) * 4 +
                             (t & 1) * 2 + (g & 1);
            uint32_t lane2;
            asm volatile("mov.u32 %0, %%laneid;" : "=r"(lane2));
#pragma unroll 1
            for (int pass = 0; pass < 2; pass++) {
                int n = pass * NCH;
                asm volatile("" : "+r"(n));
                float acc[4][4] = {};
                uint32_t psrc = sb + SM_P + t * 32;
                uint32_t va[8][4], vb[8][4] = {};
                uint32_t pt[4] = {};
                uint32_t cur[4];
#pragma unroll
                for (int j = 0; j < 4; j++) cur[j] = off[j] + s * CHUNK;
                uint32_t bar = sb + BAR_FULL + 8 * s, ready = 0;
#pragma unroll 1
                for (int i = n; i > 0; i--) {
                    if (!ready) mbar_wait(bar, ph);
                    PROF_CHUNK(2 * NCH - i);
                    const bool wrap = bar == sb + BAR_FULL + 8 * (NS - 1);
                    const uint32_t barn = wrap ? sb + BAR_FULL : bar + 8;
                    ph ^= wrap;
                    const uint4 p0 = lds128(psrc), p1 = lds128(psrc + 16);
#pragma unroll
                    for (int j = 0; j < 2; j++) ldsm4t(va[j], cur[j & 3] + (j >> 2) * 8192);
                    uint32_t tok;
                    asm volatile("{\n.reg .pred p;\nmbarrier.test_wait.parity.shared::cta.b64 p, [%2], %3;\n"
                                 "selp.u32 %0, 1, 0, p;\nselp.u32 %1, %4, %5, p;\n}"
                                 : "=r"(ready), "=r"(tok) : "r"(barn), "r"(ph), "r"(lane), "r"(lane2) : "memory");
#pragma unroll
                    for (int j = 2; j < 8; j++) ldsm4t(va[j], cur[j & 3] + (j >> 2) * 8192);
#pragma unroll
                    for (int j = 0; j < 8; j++) mma(acc[j & 3], vb[j], pt[(j >> 2) * 2], pt[(j >> 2) * 2 + 1]);
#pragma unroll
                    for (int j = 0; j < 8; j++) ldsm4t(vb[j], cur[j & 3] + (2 + (j >> 2)) * 8192);
                    asm volatile("{\n.reg .pred p;\nsetp.eq.u32 p, %1, 0;\n@p mbarrier.arrive.shared::cta.b64 _, [%0];\n}"
                                 ::"r"(bar + 8 * NS), "r"(tok) : "memory");
                    mma(acc[0], va[0], p0.x & pmask, p0.y & pmask);
                    mma(acc[1], va[1], p0.x & pmask, p0.y & pmask);
                    mma(acc[2], va[2], p0.x & pmask, p0.y & pmask);
                    mma(acc[3], va[3], p0.x & pmask, p0.y & pmask);
                    mma(acc[0], va[4], p0.z & pmask, p0.w & pmask);
                    mma(acc[1], va[5], p0.z & pmask, p0.w & pmask);
                    mma(acc[2], va[6], p0.z & pmask, p0.w & pmask);
                    mma(acc[3], va[7], p0.z & pmask, p0.w & pmask);
                    pt[0] = p1.x & pmask;
                    pt[1] = p1.y & pmask;
                    pt[2] = p1.z & pmask;
                    pt[3] = p1.w & pmask;
                    psrc += 128;
                    bar = barn;
                    const uint32_t step = wrap ? -(NS - 1) * CHUNK : CHUNK;
#pragma unroll
                    for (int j = 0; j < 4; j++) cur[j] += step;
                }
#pragma unroll
                for (int j = 0; j < 8; j++) mma(acc[j & 3], vb[j], pt[(j >> 2) * 2], pt[(j >> 2) * 2 + 1]);
                PROF_AT(tid == 0 && pass, 4);
                float ev[4], od[4];
#pragma unroll
                for (int T = 0; T < 4; T++) {
                    ev[T] = acc[T][0] + acc[T][3];
                    od[T] = acc[T][1] + acc[T][2];
                }
                ev[0] += __shfl_xor_sync(0xffffffffu, ev[1], 1);
                od[0] += __shfl_xor_sync(0xffffffffu, od[1], 1);
                ev[2] += __shfl_xor_sync(0xffffffffu, ev[3], 1);
                od[2] += __shfl_xor_sync(0xffffffffu, od[3], 1);
                ev[0] += __shfl_xor_sync(0xffffffffu, ev[2], 2);
                od[0] += __shfl_xor_sync(0xffffffffu, od[2], 2);
                const float other = __shfl_xor_sync(0xffffffffu, (g & 1) ? ev[0] : od[0], 4);
                const uint32_t w = (g & 1) ? pack_bf(other, od[0]) : pack_bf(ev[0], other);
                xst32(odst, n ? w : EMPTY);
                PROF_AT(tid == 0 && pass, 5);
                __syncwarp();
                if (!n && lane == 0) mbar_arrive(sb + BAR_DRY);
                if (c < 112) {
                    bar_sync(1, 128);
                    if (n) mbar_wait(sb + (c < 56 ? W1_GATE : W2_GATE), 0);
                    if (c < 56) {
                        const int row = tid >> 2, ch = tid & 3;
                        const uint32_t dst = sb + SM_WX + row * 64 + ((ch ^ ((row >> 1) & 3)) << 4);
                        const __nv_bfloat16* src = p.w1 + row * FF + c * 32 + ch * 8;
#pragma unroll
                        for (int i = 0; i < 14; i++) cp16(dst + i * 2048, src + i * 32 * FF, n);
                    } else {
                        const int row = tid >> 1, ch = tid & 1;
                        const uint32_t dst = sb + SM_WX + row * 32 + ((ch ^ ((row >> 2) & 1)) << 4);
                        const __nv_bfloat16* src = p.w2 + row * DM + ((c - 56) % 28) * 16 + ch * 8;
#pragma unroll
                        for (int i = 0; i < 28; i++) cp16(dst + i * 2048, src + i * 64 * DM, n);
                    }
                    cp_commit();
                    cp_wait<0>();
                    __syncwarp();
                    if (n && lane == 0) mbar_arrive(sb + BAR_W1);
                }
            }
        }
    } else {
        const int ew = warp - 5, et = tid - 160;
        const int g = lane >> 2, t = lane & 3, r = lane & 7, mi = lane >> 3;
        {
            uint32_t w[7];
#pragma unroll
            for (int i = 0; i < 7; i++)
                asm volatile("ld.global.nc.u32 %0, [%1];" : "=r"(w[i]) : "l"((const uint32_t*)p.x + ew * 224 + i * 32 + lane));
            __syncthreads();
            PROF_AT(et == 0, 24);
            PROF_AT(et == 0 && w[0] + w[6] != 0x12345, 25);
            layernorm_row(w, sb + SM_XN + ew * 912, lane);
            PROF_AT(et == 0, 26);
            mbar_wait(sb + BAR_WQ, 0);
            PROF_AT(et == 0, 27);
            uint32_t a[8][4];
            frags_w448(a, sb + SM_WQ, ew, lane);
            const float2 q = gemv448(a, sb, ew, lane, et);
            if (et < 128) {
                xst32(gx->q + ((et >> 4) * 16 + (c >> 3)) * 128 + (c & 7) * 16 + (et & 15), ~pack_bf(q.x, q.y));
                asm volatile("bar.arrive 3, 256;" ::: "memory");
            }
            PROF_AT(et == 0, 1);
        }
        const int hh = c / 7, jj = c - hh * 7;
        const bool is_f1 = c < 56;
        const int cg = (c - 56) % 28, half = (c - 56) / 28;
        const int hk = c - 112, hb = (ew >> 1) * 2 + (mi & 1);
        uint32_t side = 0;
        if (c < 126)
            asm volatile("ld.global.nc.u32 %0, [%1];" : "=r"(side)
                         : "l"(is_f1 ? p.b1 + c * 32 + (et & 15) * 2
                                     : c < 112 ? p.b2 + cg * 16 + r * 2 : p.x + hb * DM + hk * 32 + (r & 3) * 8 + (ew & 1) * 4 + (r >> 2) * 2));
        uint32_t seen_prog = 0;
#pragma unroll 1
        for (int pass = 0; pass < 2; pass++) {
            uint32_t live = pass;
            asm volatile("" : "+r"(live));
            const uint32_t want = 0u - live, wipe = ~want;
            if (et == 0) {
                if (!live) mbar_wait(sb + BAR_Q, 0);
#pragma unroll 1
                for (int it = 0; it < SPIN_LIMIT; it++) {
                    const uint32_t prog = lds32(sb + SM_PROG);
                    int total = 0;
                    if (prog == seen_prog) __nanosleep(MON_SLEEP);
                    if (prog != seen_prog || prog >= 2 * NCH - 8)
                        asm volatile("ld.relaxed.gpu.global.u32 %0, [%1];" : "=r"(total) : "l"(gx->count + 32) : "memory");
                    if (total >= ALL_CHUNKS - LIFT_LEFT) {
                        sts32(sb + SM_DEPTH, NS);
                    } else if (prog != seen_prog) {
                        const int lead = prog * NCTA - total;
                        sts32(sb + SM_DEPTH, lead >= LEAD1 ? 1 : lead >= LEAD2 ? 2 : lead >= LEAD2 - 128 ? 3 : lead >= LEAD2 - 256 ? 4 : NS);
                    }
                    seen_prog = prog;
                    if (live ? total >= ALL_CHUNKS - TRIG_LEFT || (c >= 126 && prog == 2 * NCH) : mbar_test(sb + BAR_DRY, 0)) break;
                }
            } else if (et == 32 && live) {
                uint32_t seen;
                mbar_wait(sb + BAR_DRY, 0);
                asm volatile("atom.release.gpu.global.add.u32 %0, [%1], 1;" : "=r"(seen) : "l"(gx->count) : "memory");
                int it = 0;
                for (seen++; c < 126 && seen < NCTA && ++it < SPIN_LIMIT;) {
                    __nanosleep(512);
                    asm volatile("ld.relaxed.gpu.global.u32 %0, [%1];" : "=r"(seen) : "l"(gx->count) : "memory");
                }
                asm volatile("ld.acquire.gpu.global.u32 %0, [%1];" : "=r"(seen) : "l"(gx->count) : "memory");
                PROF_AT(true, 22);
            }
            __syncwarp();
            if (c >= 126) continue;
            bar_sync(2, 256);
            PROF_AT(et == 0, live ? 6 : 18);
            if (c >= 112) {
                const bool odd = mi & 1;
                float a0, a1;
                uint32_t* const dst = gx->h + pin((((mi >> 1) * 14 + hk) * 8 + hb) * 16 + (ew & 1) * 8 + r);
                poll128<4, 128>(gx->part + pin((hk * 8 + ew) * 512 + lane * 4), want, want, [&](const uint4 (&v)[4]) {
                    const float f0 = (__uint_as_float(v[0].x) + __uint_as_float(v[1].x)) + (__uint_as_float(v[2].x) + __uint_as_float(v[3].x));
                    const float f1 = (__uint_as_float(v[0].y) + __uint_as_float(v[1].y)) + (__uint_as_float(v[2].y) + __uint_as_float(v[3].y));
                    const float f2 = (__uint_as_float(v[0].z) + __uint_as_float(v[1].z)) + (__uint_as_float(v[2].z) + __uint_as_float(v[3].z));
                    const float f3 = (__uint_as_float(v[0].w) + __uint_as_float(v[1].w)) + (__uint_as_float(v[2].w) + __uint_as_float(v[3].w));
                    a0 = (odd ? f1 : f0) + __shfl_xor_sync(0xffffffffu, odd ? f0 : f1, 8);
                    a1 = (odd ? f3 : f2) + __shfl_xor_sync(0xffffffffu, odd ? f2 : f3, 8);
                    a0 += __shfl_xor_sync(0xffffffffu, a0, 16);
                    a1 += __shfl_xor_sync(0xffffffffu, a1, 16);
                });
                xst32(dst, bf2_add(side, pack_bf(a0, a1)) | wipe);
                PROF_AT(et == 0 && live, 9);
                if (!live) bar_sync(2, 256);
                continue;
            }
            {
                const int lz = pin(lane);
                const int row = ew * 32 + (lz >> 3), ch = lz & 7;
                const uint32_t dst = sb + SM_WO + row * 128 + ((ch ^ (lz >> 3)) << 4);
                const __nv_bfloat16* src = p.wo + (hh * 256 + row) * DM + jj * 64 + ch * 8;
#pragma unroll
                for (int i = 0; i < 8; i++) cp16((dst ^ ((i & 1) << 6)) + i * 512, src + i * 4 * DM, live);
                asm volatile("{\n.reg .pred p;\nsetp.ne.u32 p, %2, 0;\n@p cp.async.mbarrier.arrive.noinc.shared::cta.b64 [%0];\n"
                             "@p cp.async.mbarrier.arrive.noinc.shared::cta.b64 [%1];\n}"
                             ::"r"(sb + BAR_WO + 8 * ew), "r"(sb + BAR_W0), "r"(live) : "memory");
                uint32_t fa[4];
#pragma unroll
                for (int mt = 0; mt < 4; mt++)
                    fa[mt] = pin(sb + SM_WO + (ew * 32 + (mi >> 1) * 8 + r) * 128 + (((2 * mt + (mi & 1)) ^ r) << 4));
                const uint32_t wb = pin(sb + SM_RED + (ew * 544 + t * 136 + g * 2) * 4);
                const uint32_t rb = pin(sb + SM_RED + ((ew & 3) * 136 + ((ew >> 2) * 32 + (r >> 1) * 8 + mi * 2 + (r & 1)) * 2) * 4);
                const uint32_t* osrc = gx->o + pin((hh * 8 + g) * 128 + ew * 16 + t * 4);
                uint32_t* const pdst = gx->part + pin((((jj * 8 + ew) * 2 + (lane >> 4)) * 16 + hh) * 32 + (lane & 15) * 2);
                const uint32_t gate = sb + (live ? BAR_WO + 8 * ew : BAR_DRY);
                uint4 o = make_uint4(want, want, want, want);
                uint32_t top = want;
                int left = SPIN_LIMIT;
                bool pending;
#pragma unroll 1
                do {
                    xld128(o, osrc, top);
                    top = top_word(o);
                    left--;
                    pending = __any_sync(0xffffffffu, top == EMPTY && left > 0);
                } while (pending && !mbar_test(gate, 0));
                mbar_wait(gate, 0);
                PROF_AT(et == 0 && live, 7);
                if (PF_MODE && et == 0 && live) {
                    if (PF_MODE == 2) asm volatile("cp.async.bulk.prefetch.L2.global [%0], 14336;" ::"l"(p.w1 + c * 7168) : "memory");
                    asm volatile("cp.async.bulk.prefetch.L2.global [%0], 14336;" ::"l"(p.w2 + c * 7168) : "memory");
                }
                uint32_t a[8][4];
#pragma unroll
                for (int mt = 0; mt < 4; mt++) ldsm4t(a[mt], fa[mt]);
#pragma unroll
                for (int mt = 0; mt < 4; mt++) ldsm4t(a[4 + mt], fa[mt] + 2048);
                float acc[4][4];
#pragma unroll 1
                do {
                    xld128(o, osrc, top);
                    top = top_word(o);
                    left--;
                    pending = __any_sync(0xffffffffu, top == EMPTY && left > 0);
#pragma unroll
                    for (int mt = 0; mt < 4; mt++) mma0(acc[mt], a[mt], o.x, o.y);
#pragma unroll
                    for (int mt = 0; mt < 4; mt++) mma(acc[mt], a[4 + mt], o.z, o.w);
                } while (pending);
                PROF_AT(et == 0 && live, 8);
#pragma unroll
                for (int mt = 0; mt < 4; mt++) {
                    sts64f(wb + mt * 128, acc[mt][0], acc[mt][1]);
                    sts64f(wb + mt * 128 + 64, acc[mt][2], acc[mt][3]);
                }
                bar_sync(2, 256);
                float2 v[8];
#pragma unroll
                for (int w = 0; w < 8; w++) v[w] = lds64f(rb + w * 2176);
                const float s0 = ((v[0].x + v[1].x) + (v[2].x + v[3].x)) + ((v[4].x + v[5].x) + (v[6].x + v[7].x));
                const float s1 = ((v[0].y + v[1].y) + (v[2].y + v[3].y)) + ((v[4].y + v[5].y) + (v[6].y + v[7].y));
                xst64(pdst, __float_as_uint(s0) | wipe, __float_as_uint(s1) | wipe);
            }
            if (et == 0 && live) mbar_arrive(sb + BAR_E1);
            PROF_AT(et == 0 && live, 13);
            mbar_wait(sb + (live ? BAR_W1 : BAR_DRY), 0);
            PROF_AT(et == 32 && live, 15);
            if (is_f1) {
                constexpr uint32_t ONES = 0x3f803f80u;
                if (ew < 7) {
                    uint32_t a[8][4];
                    frags_w448(a, sb + SM_WX, ew, lane);
                    float cs[2][4] = {};
#pragma unroll
                    for (int ks = 0; ks < 4; ks++) {
                        mma(cs[0], a[ks * 2], ONES, ONES);
                        mma(cs[1], a[ks * 2 + 1], ONES, ONES);
                    }
                    if (t == 0) {
                        const uint32_t cb = sb + SM_XN + (ew * 32 + g) * 4;
                        sts32f(cb, cs[0][0]);
                        sts32f(cb + 32, cs[0][2]);
                        sts32f(cb + 64, cs[1][0]);
                        sts32f(cb + 96, cs[1][2]);
                    }
                    bar_sync(4, 224);
                    float2 colsum = make_float2(0.f, 0.f);
#pragma unroll
                    for (int w = 0; w < 7; w++) {
                        const float2 x = lds64f(sb + SM_XN + (w * 32 + (et & 15) * 2) * 4);
                        colsum.x += x.x;
                        colsum.y += x.y;
                    }
                    const int b = (et >> 4) & 7, pr = et & 15;
                    const uint32_t wb = pin(sb + SM_RED + (ew * 288 + t * 72 + g) * 4);
                    const uint32_t sw = pin(sb + SM_RED + (ew * 288 + g * 36 + (t == (g >> 1) ? 32 : 34)) * 4);
                    const uint32_t rs = pin(sb + SM_RED + b * 144 + 128), rz = pin(sb + SM_RED + b * 144 + pr * 8);
                    const bool odd = pin(g & 1);
                    uint32_t* const dst = gx->r + pin((((b >> 2) * 56 + c) * 4 + (b & 3)) * 16 + (pr & 3) * 4 + (pr >> 2));
                    if (H_SLEEP && live) __nanosleep(H_SLEEP);
                    float z[2][4], st[4];
                    poll128<2, 128>(gx->h + pin(((c & 1) * 14 + ew * 2) * 128 + lane * 4), want, want, [&](const uint4 (&v)[2]) {
#pragma unroll
                        for (int ks = 0; ks < 4; ks++) {
                            const uint32_t b0 = (ks & 1) ? v[ks >> 1].z : v[ks >> 1].x, b1 = (ks & 1) ? v[ks >> 1].w : v[ks >> 1].y;
                            const uint32_t sa[4] = {b0, ONES, b1, ONES};
                            if (ks == 0) {
                                mma0(st, sa, b0, b1);
                                mma0(z[0], a[0], b0, b1);
                                mma0(z[1], a[1], b0, b1);
                            } else {
                                mma(st, sa, b0, b1);
                                mma(z[0], a[ks * 2], b0, b1);
                                mma(z[1], a[ks * 2 + 1], b0, b1);
                            }
                        }
                    });
                    PROF_AT(et == 0 && live, 10);
                    sts64f(sw, odd ? st[3] : st[2], odd ? st[1] : st[0]);
#pragma unroll
                    for (int mt = 0; mt < 2; mt++) {
                        sts32f(wb + mt * 64, z[mt][0]);
                        sts32f(wb + mt * 64 + 144, z[mt][1]);
                        sts32f(wb + mt * 64 + 32, z[mt][2]);
                        sts32f(wb + mt * 64 + 176, z[mt][3]);
                    }
                    bar_sync(4, 224);
                    if (ew < 4) {
                        float2 sv[7], zv[7];
#pragma unroll
                        for (int w = 0; w < 7; w++) sv[w] = lds64f(rs + w * 1152);
#pragma unroll
                        for (int w = 0; w < 7; w++) zv[w] = lds64f(rz + w * 1152);
                        const float mu = (((sv[0].x + sv[1].x) + (sv[2].x + sv[3].x)) + ((sv[4].x + sv[5].x) + sv[6].x)) * (1.f / DM);
                        const float sq = ((sv[0].y + sv[1].y) + (sv[2].y + sv[3].y)) + ((sv[4].y + sv[5].y) + sv[6].y);
                        const float inv = inv_std(bf_round(fmaxf(fmaf(sq, 1.f / DM, -mu * mu), 0.f)));
                        const float mean = bf_round(mu);
                        const float z0 = ((zv[0].x + zv[1].x) + (zv[2].x + zv[3].x)) + ((zv[4].x + zv[5].x) + zv[6].x);
                        const float z1 = ((zv[0].y + zv[1].y) + (zv[2].y + zv[3].y)) + ((zv[4].y + zv[5].y) + zv[6].y);
                        const uint32_t u = pack_bf(fmaf(-mean, colsum.x, z0) * inv, fmaf(-mean, colsum.y, z1) * inv);
                        xst32(dst, bf2_relu_sq(bf2_add(u, side)) | wipe);
                    }
                    PROF_AT(et == 0 && live, 11);
                }
            } else {
                uint32_t a[14][4];
                const uint32_t base = sb + SM_WX + (ew * 224 + (mi >> 1) * 8 + r) * 32 + (((mi & 1) ^ (r >> 2)) << 4);
#pragma unroll
                for (int ks = 0; ks < 14; ks++) ldsm4t(a[ks], base + ks * 512);
                const uint32_t wb = pin(sb + SM_XN + (ew * 160 + (t & 1) * 80 + (g >> 1) * 4 + (t >> 1) * 2 + (g & 1)) * 4);
                const uint32_t rb = pin(sb + SM_XN + (mi * 40 + r * 4) * 4);
                const bool upper = pin(t >> 1);
                uint32_t* const dst = (live ? (uint32_t*)p.out : gx->sink) + pin((half * 4 + mi) * 224 + cg * 8 + r);
                const uint32_t* rsrc = gx->r + pin((half * 56 + ew * 7) * 64 + lane * 4);
                const uint32_t hres = poll32(gx->h + pin((((c & 1) * 14 + (cg >> 1)) * 8 + half * 4 + mi) * 16 + (r & 3) * 4 +
                                                         (cg & 1) * 2 + (r >> 2)), want, EMPTY);
                PROF_AT(et == 0 && live, 16);
                if (R_SLEEP && live) __nanosleep(R_SLEEP);
                float acc[4][4];
                poll128<4, 128>(rsrc, want, lane < 16 ? want : 0u, [&](const uint4 (&v)[4]) {
                    mma0(acc[0], a[0], v[0].x, v[0].y);
                    mma0(acc[1], a[1], v[0].z, v[0].w);
                    mma0(acc[2], a[2], v[0].x, v[0].y);
                    mma0(acc[3], a[3], v[0].z, v[0].w);
#pragma unroll
                    for (int i = 1; i < 4; i++) {
                        mma(acc[0], a[4 * i], v[i].x, v[i].y);
                        mma(acc[1], a[4 * i + 1], v[i].z, v[i].w);
                        if (i < 3) {
                            mma(acc[2], a[4 * i + 2], v[i].x, v[i].y);
                            mma(acc[3], a[4 * i + 3], v[i].z, v[i].w);
                        }
                    }
                });
                PROF_AT(et == 0 && live, 17);
                sts32f(wb, upper ? acc[2][0] + acc[3][0] : acc[0][0] + acc[1][0]);
                sts32f(wb + 160, upper ? acc[2][1] + acc[3][1] : acc[0][1] + acc[1][1]);
                sts32f(wb + 64, upper ? acc[2][2] + acc[3][2] : acc[0][2] + acc[1][2]);
                sts32f(wb + 224, upper ? acc[2][3] + acc[3][3] : acc[0][3] + acc[1][3]);
                if (ew == 0) {
                    bar_sync(2, 256);
                    float x[8], y[8];
#pragma unroll
                    for (int w = 0; w < 8; w++) {
                        const uint4 q = lds128(rb + w * 640);
                        x[w] = __uint_as_float(q.x) + __uint_as_float(q.z);
                        y[w] = __uint_as_float(q.y) + __uint_as_float(q.w);
                    }
                    const float s0 = ((x[0] + x[1]) + (x[2] + x[3])) + ((x[4] + x[5]) + (x[6] + x[7]));
                    const float s1 = ((y[0] + y[1]) + (y[2] + y[3])) + ((y[4] + y[5]) + (y[6] + y[7]));
                    *dst = bf2_add(hres, bf2_add(pack_bf(s0, s1), side));
                    PROF_AT(et == 0 && live, 12);
                } else {
                    asm volatile("bar.arrive 2, 256;" ::: "memory");
                    if (c == 56 && et == 32 && live) {
                        xst32(gx->count, 0);
                        xst32(gx->count + 32, 0);
                    }
                }
            }
            if (!live) bar_sync(5, 256);
            PROF_AT(et == 0 && !live, 19);
        }
    }
}

}

extern "C" void kernel_launch(void* const* d_in, const int* in_sizes, int n_in, void* d_out, int out_size) {
    (void)in_sizes; (void)n_in; (void)out_size;
    Params p;
    p.x = (const __nv_bfloat16*)d_in[0];
    p.k = (const __nv_bfloat16*)d_in[1];
    p.v = (const __nv_bfloat16*)d_in[2];
    p.wq = (const __nv_bfloat16*)d_in[3];
    p.wo = (const __nv_bfloat16*)d_in[4];
    p.w1 = (const __nv_bfloat16*)d_in[6];
    p.b1 = (const __nv_bfloat16*)d_in[7];
    p.w2 = (const __nv_bfloat16*)d_in[8];
    p.b2 = (const __nv_bfloat16*)d_in[9];
    p.out = (__nv_bfloat16*)d_out;
    cudaGetSymbolAddress((void**)&p.xch, g_x);
    cudaFuncSetAttribute(fused_decode_kernel, cudaFuncAttributeMaxDynamicSharedMemorySize, SM_TOTAL);
    fused_decode_kernel<<<NCTA, NTHREADS, SM_TOTAL>>>(p);
}
```

```cpp
#include <cuda.h>
#include <cuda_runtime.h>
#include <cuda_bf16.h>
#include <stdint.h>

namespace {

constexpr int DM = 448, NH = 16, SK = 4096, DH = 256, FF = 1792;
constexpr int NCTA = 128;
constexpr int CHUNK = 32768;
constexpr int NCH = SK / 64;
constexpr int NS = 5;
constexpr int ALL_CHUNKS = NCTA * 2 * NCH;
#define TRIG_LEFT 220
#define LIFT_LEFT 350
#define LEAD1 256
#define LEAD2 -128
#define MON_SLEEP 100
#define W1_GATE BAR_W0
#define W2_GATE BAR_E1
#define W2_DELAY 700
#define L2PROMO CU_TENSOR_MAP_L2_PROMOTION_L2_128B
#define TOP_START 1
#define HEADB 8192
#define K0_DELAY 0
#define K1_DELAY 2000
#define PF_EARLY 0
#define PF_GATE BAR_W0
#define ROT 32
#define LSTEP 128
#define WQH 0
#define WQ_HINT ""
#define NO_W 0
#define W1_DELAY 600
#define PF_DELAY 500
#define PF_MODE 3
constexpr int HEAD_BYTES = HEADB;
constexpr int NTHREADS = 13 * 32;
constexpr int SPIN_LIMIT = 1 << 20;

constexpr int SM_RING = 0;
constexpr int SM_WX = 0;
constexpr int SM_WQ = NS * CHUNK;
constexpr int SM_WO = SM_WQ;
constexpr int SM_P = SM_WQ + 32768;
constexpr int SM_RED = SM_P + 8192;
constexpr int SM_XN = SM_RED + 8 * 544 * 4;
constexpr int SM_Q = SM_XN + 8 * 456 * 2;
constexpr int SM_STAT = SM_Q + 512;
constexpr int SM_PROG = SM_STAT + 32, SM_DEPTH = SM_STAT + 36;
constexpr int SM_BAR = SM_STAT + 64;
constexpr int BAR_FULL = SM_BAR, BAR_EMPTY = BAR_FULL + 8 * NS, BAR_WO = BAR_EMPTY + 8 * NS, BAR_DRY = BAR_WO + 64,
              BAR_WQ = BAR_DRY + 8, BAR_Q = BAR_WQ + 8, BAR_W0 = BAR_WO + 56, BAR_E1 = BAR_Q + 8, BAR_W1 = BAR_E1 + 8;
constexpr int SM_TOTAL = BAR_W1 + 64;
static_assert(SM_TOTAL <= 232448, "shared memory budget");

struct Exchange {
    uint32_t q[NCTA * 128];
    uint32_t o[NH * 8 * 128];
    uint32_t part[14 * 8 * 16 * 32];
    uint32_t h[2 * 14 * 8 * 16];
    uint32_t r[2 * 56 * 4 * 16];
    uint32_t count[64];
    uint32_t sink[8 * 224];
};
__device__ __align__(128) Exchange g_x;

#define PROF_AT(cond, slot) do { } while (0)
#define PROF_CHUNK(i) do { } while (0)

__device__ __forceinline__ void mbar_init(uint32_t bar, uint32_t count) {
    asm volatile("mbarrier.init.shared::cta.b64 [%0], %1;" ::"r"(bar), "r"(count) : "memory");
}
__device__ __forceinline__ void mbar_arrive(uint32_t bar) {
    asm volatile("mbarrier.arrive.shared::cta.b64 _, [%0];" ::"r"(bar) : "memory");
}
__device__ __forceinline__ void mbar_expect_tx(uint32_t bar, uint32_t bytes) {
    asm volatile("mbarrier.arrive.expect_tx.shared::cta.b64 _, [%0], %1;" ::"r"(bar), "r"(bytes) : "memory");
}
__device__ __forceinline__ void mbar_wait(uint32_t bar, uint32_t parity) {
    uint32_t done;
    int it = 0;
    do {
        asm volatile("{\n.reg .pred p;\nmbarrier.try_wait.parity.shared::cta.b64 p, [%1], %2;\nselp.u32 %0, 1, 0, p;\n}"
                     : "=r"(done) : "r"(bar), "r"(parity) : "memory");
    } while (!done && ++it < SPIN_LIMIT);
}
__device__ __forceinline__ uint32_t mbar_test(uint32_t bar, uint32_t parity) {
    uint32_t done;
    asm volatile("{\n.reg .pred p;\nmbarrier.test_wait.parity.shared::cta.b64 p, [%1], %2;\nselp.u32 %0, 1, 0, p;\n}"
                 : "=r"(done) : "r"(bar), "r"(parity) : "memory");
    return done;
}
__device__ __forceinline__ void bulk_load(uint32_t dst, const void* src, uint32_t bytes, uint32_t bar, uint64_t pol) {
    asm volatile("cp.async.bulk.shared::cluster.global.mbarrier::complete_tx::bytes.L2::cache_hint [%0], [%1], %2, [%3], %4;"
                 ::"r"(dst), "l"(src), "r"(bytes), "r"(bar), "l"(pol) : "memory");
}
__device__ __forceinline__ void tile_loads(uint32_t dst, const CUtensorMap* map, int col, int row, int rows, uint32_t bytes,
                                           uint32_t bar, int n) {
#pragma unroll 1
    for (int i = 0; i < n; i++, dst += bytes, row += rows, bar += 8) {
        mbar_expect_tx(bar, bytes);
        asm volatile("cp.async.bulk.tensor.2d.shared::cluster.global.mbarrier::complete_tx::bytes [%0], [%1, {%2, %3}], [%4];"
                     ::"r"(dst), "l"(map), "r"(col), "r"(row), "r"(bar) : "memory");
    }
}
__device__ __forceinline__ void bar_sync(int id, int n) { asm volatile("bar.sync %0, %1;" ::"r"(id), "r"(n) : "memory"); }

__device__ __forceinline__ void ldsm4(uint32_t (&r)[4], uint32_t a) {
    asm volatile("ldmatrix.sync.aligned.m8n8.x4.shared.b16 {%0,%1,%2,%3}, [%4];"
                 : "=r"(r[0]), "=r"(r[1]), "=r"(r[2]), "=r"(r[3]) : "r"(a) : "memory");
}
__device__ __forceinline__ void ldsm4t(uint32_t (&r)[4], uint32_t a) {
    asm volatile("ldmatrix.sync.aligned.m8n8.x4.trans.shared.b16 {%0,%1,%2,%3}, [%4];"
                 : "=r"(r[0]), "=r"(r[1]), "=r"(r[2]), "=r"(r[3]) : "r"(a) : "memory");
}
__device__ __forceinline__ void mma(float (&c)[4], const uint32_t (&a)[4], uint32_t b0, uint32_t b1) {
    asm volatile("mma.sync.aligned.m16n8k16.row.col.f32.bf16.bf16.f32 {%0,%1,%2,%3}, {%4,%5,%6,%7}, {%8,%9}, {%0,%1,%2,%3};"
                 : "+f"(c[0]), "+f"(c[1]), "+f"(c[2]), "+f"(c[3])
                 : "r"(a[0]), "r"(a[1]), "r"(a[2]), "r"(a[3]), "r"(b0), "r"(b1));
}
__device__ __forceinline__ void mma0(float (&c)[4], const uint32_t (&a)[4], uint32_t b0, uint32_t b1) {
    asm volatile("mma.sync.aligned.m16n8k16.row.col.f32.bf16.bf16.f32 {%0,%1,%2,%3}, {%4,%5,%6,%7}, {%8,%9}, {%10,%10,%10,%10};"
                 : "=f"(c[0]), "=f"(c[1]), "=f"(c[2]), "=f"(c[3])
                 : "r"(a[0]), "r"(a[1]), "r"(a[2]), "r"(a[3]), "r"(b0), "r"(b1), "f"(0.f));
}
__device__ __forceinline__ uint32_t lds32(uint32_t a) {
    uint32_t v;
    asm volatile("ld.shared.u32 %0, [%1];" : "=r"(v) : "r"(a) : "memory");
    return v;
}
__device__ __forceinline__ float2 lds64f(uint32_t a) {
    float2 v;
    asm volatile("ld.shared.v2.f32 {%0,%1}, [%2];" : "=f"(v.x), "=f"(v.y) : "r"(a) : "memory");
    return v;
}
__device__ __forceinline__ uint4 lds128(uint32_t a) {
    uint4 v;
    asm volatile("ld.shared.v4.u32 {%0,%1,%2,%3}, [%4];" : "=r"(v.x), "=r"(v.y), "=r"(v.z), "=r"(v.w) : "r"(a) : "memory");
    return v;
}
__device__ __forceinline__ void sts16(uint32_t a, uint32_t v) {
    asm volatile("st.shared.u16 [%0], %1;" ::"r"(a), "h"((unsigned short)v) : "memory");
}
__device__ __forceinline__ void sts32(uint32_t a, uint32_t v) {
    asm volatile("st.shared.u32 [%0], %1;" ::"r"(a), "r"(v) : "memory");
}
__device__ __forceinline__ void sts32f(uint32_t a, float v) {
    asm volatile("st.shared.f32 [%0], %1;" ::"r"(a), "f"(v) : "memory");
}
__device__ __forceinline__ void sts64f(uint32_t a, float x, float y) {
    asm volatile("st.shared.v2.f32 [%0], {%1,%2};" ::"r"(a), "f"(x), "f"(y) : "memory");
}
__device__ __forceinline__ void sts128(uint32_t a, uint4 v) {
    asm volatile("st.shared.v4.u32 [%0], {%1,%2,%3,%4};" ::"r"(a), "r"(v.x), "r"(v.y), "r"(v.z), "r"(v.w) : "memory");
}

constexpr uint32_t EMPTY = 0xffffffffu;
__device__ __forceinline__ void xld32(uint32_t& v, const uint32_t* p, uint32_t empty) {
    asm volatile("{\n.reg .pred p;\nsetp.eq.u32 p, %0, %2;\n@p ld.relaxed.gpu.global.u32 %0, [%1];\n}"
                 : "+r"(v) : "l"(p), "r"(empty) : "memory");
}
__device__ __forceinline__ void xld128(uint4& v, const uint32_t* p, uint32_t top) {
    asm volatile("{\n.reg .pred p;\nsetp.eq.u32 p, %5, 0xffffffff;\n@p ld.relaxed.gpu.global.v4.u32 {%0,%1,%2,%3}, [%4];\n}"
                 : "+r"(v.x), "+r"(v.y), "+r"(v.z), "+r"(v.w) : "l"(p), "r"(top) : "memory");
}
__device__ __forceinline__ void xst32(uint32_t* p, uint32_t v) {
    asm volatile("st.relaxed.gpu.global.u32 [%0], %1;" ::"l"(p), "r"(v) : "memory");
}
__device__ __forceinline__ void xst64(uint32_t* p, uint32_t a, uint32_t b) {
    asm volatile("st.relaxed.gpu.global.v2.u32 [%0], {%1,%2};" ::"l"(p), "r"(a), "r"(b) : "memory");
}
__device__ __forceinline__ uint32_t top_word(const uint4& v) { return max(__vimax3_u32(v.x, v.y, v.z), v.w); }
template <int N, int STRIDE, class F>
__device__ __forceinline__ void poll128(uint4 (&v)[N], const uint32_t* src, uint32_t init, uint32_t init_last, F use,
                                        const uint32_t* xsrc = nullptr, uint32_t* extra = nullptr) {
    uint32_t m[N];
#pragma unroll
    for (int i = 0; i < N; i++) {
        m[i] = i == N - 1 ? init_last : init;
        v[i] = make_uint4(m[i], m[i], m[i], m[i]);
    }
    int left = SPIN_LIMIT;
    bool again;
#pragma unroll 1
    do {
#pragma unroll
        for (int i = 0; i < N; i++) xld128(v[i], src + i * STRIDE, m[i]);
        if (extra) xld32(*extra, xsrc, EMPTY);
        left--;
        uint32_t top = extra ? *extra : 0;
#pragma unroll
        for (int i = 0; i < N; i++) {
            m[i] = top_word(v[i]);
            top = max(top, m[i]);
        }
        again = __any_sync(0xffffffffu, top == EMPTY && left > 0);
        use(v);
    } while (again);
}
__device__ __forceinline__ uint32_t poll32(const uint32_t* src, uint32_t init, uint32_t empty) {
    int left = SPIN_LIMIT;
#pragma unroll 1
    do {
        xld32(init, src, empty);
        left--;
    } while (__any_sync(0xffffffffu, init == empty && left > 0));
    return init;
}
__device__ __forceinline__ uint32_t pin(uint32_t v) {
    asm volatile("shfl.sync.bfly.b32 %0, %0, 0, 0x1f, 0xffffffff;" : "+r"(v));
    return v;
}
__device__ __forceinline__ uint32_t bf2_add(uint32_t a, uint32_t b) {
    uint32_t r;
    asm("add.rn.bf16x2 %0, %1, %2;" : "=r"(r) : "r"(a), "r"(b));
    return r;
}
__device__ __forceinline__ uint32_t bf2_relu_sq(uint32_t a) {
    uint32_t r;
    asm("{\n.reg .b32 m;\nmax.bf16x2 m, %1, %2;\nmul.rn.bf16x2 %0, m, m;\n}" : "=r"(r) : "r"(a), "r"(0));
    return r;
}

__device__ __forceinline__ uint32_t pack_bf(float lo, float hi) {
    uint32_t r;
    asm("cvt.rn.bf16x2.f32 %0, %1, %2;" : "=r"(r) : "f"(hi), "f"(lo));
    return r;
}
__device__ __forceinline__ float bf_round(float v) { return __uint_as_float(pack_bf(0.f, v)); }
__device__ __forceinline__ float bf_lo(uint32_t w) { return __uint_as_float(w << 16); }
__device__ __forceinline__ float bf_hi(uint32_t w) { return __uint_as_float(w & 0xffff0000u); }

__device__ __forceinline__ float inv_std(float var) {
    float sd, inv;
    asm("sqrt.approx.ftz.f32 %0, %1;" : "=f"(sd) : "f"(bf_round(var + 1e-5f)));
    asm("rcp.approx.ftz.f32 %0, %1;" : "=f"(inv) : "f"(bf_round(sd)));
    return inv;
}

__device__ __forceinline__ void layernorm_row(const uint32_t (&w)[7], uint32_t dst, int lane) {
    const float shift = bf_lo(__shfl_sync(0xffffffffu, w[0], 0));
    float s = 0.f, ss = 0.f;
#pragma unroll
    for (int i = 0; i < 7; i++) {
        const float a = bf_lo(w[i]) - shift, b = bf_hi(w[i]) - shift;
        s += a + b;
        ss = fmaf(a, a, fmaf(b, b, ss));
    }
#pragma unroll
    for (int o = 16; o; o >>= 1) {
        s += __shfl_xor_sync(0xffffffffu, s, o);
        ss += __shfl_xor_sync(0xffffffffu, ss, o);
    }
    const float md = s * (1.f / DM);
    const float mean = bf_round(shift + md);
    const float inv = inv_std(bf_round(fmaxf(ss * (1.f / DM) - md * md, 0.f)));
#pragma unroll
    for (int i = 0; i < 7; i++) {
        const float a = bf_round(bf_lo(w[i]) - mean) * inv, b = bf_round(bf_hi(w[i]) - mean) * inv;
        sts32(dst + (i * 32 + lane) * 4, pack_bf(a, b));
    }
}

__device__ __forceinline__ void frags_w448(uint32_t (&a)[8][4], uint32_t src, int ew, int lane) {
    const int r = lane & 7, mi = lane >> 3;
    const uint32_t base = src + ((ew < 7 ? ew : 0) * 64 + (mi >> 1) * 8 + r) * 64;
#pragma unroll
    for (int ks = 0; ks < 4; ks++)
#pragma unroll
        for (int mt = 0; mt < 2; mt++)
            ldsm4t(a[ks * 2 + mt], base + ks * 1024 + (((2 * mt + (mi & 1)) ^ (r >> 1)) << 4));
}
__device__ __forceinline__ float2 gemv448(const uint32_t (&a)[8][4], uint32_t sb, int ew, int lane, int et) {
    const int g = lane >> 2, t = lane & 3;
    bar_sync(2, 256);
    if (ew < 7) {
        float c[4][4] = {};
        const uint32_t xb = sb + SM_XN + (g * 228 + ew * 32 + t) * 4;
#pragma unroll
        for (int ks = 0; ks < 4; ks++) {
            const uint32_t b0 = lds32(xb + ks * 32), b1 = lds32(xb + ks * 32 + 16);
            mma(c[(ks & 1) * 2], a[ks * 2], b0, b1);
            mma(c[(ks & 1) * 2 + 1], a[ks * 2 + 1], b0, b1);
        }
        const uint32_t rb = sb + SM_RED + (ew * 288 + t * 72 + g) * 4;
#pragma unroll
        for (int mt = 0; mt < 2; mt++) {
            sts32f(rb + mt * 64, c[mt][0] + c[2 + mt][0]);
            sts32f(rb + mt * 64 + 144, c[mt][1] + c[2 + mt][1]);
            sts32f(rb + mt * 64 + 32, c[mt][2] + c[2 + mt][2]);
            sts32f(rb + mt * 64 + 176, c[mt][3] + c[2 + mt][3]);
        }
    }
    bar_sync(2, 256);
    float2 acc = make_float2(0.f, 0.f);
    if (et < 128) {
        const uint32_t rb = sb + SM_RED + ((et >> 4) * 36 + (et & 15) * 2) * 4;
#pragma unroll
        for (int w = 0; w < 7; w++) {
            const float2 v = lds64f(rb + w * 1152);
            acc.x += v.x;
            acc.y += v.y;
        }
    }
    return acc;
}

struct Params {
    int first_tid;
    const __nv_bfloat16 *x, *k, *v, *wq, *wo, *w1, *b1, *w2, *b2;
    __nv_bfloat16* out;
    Exchange* xch;
    alignas(64) CUtensorMap map_wo, map_w1, map_w2;
};

__global__ void __launch_bounds__(NTHREADS, 1) fused_decode_kernel(const __grid_constant__ Params p) {
    extern __shared__ __align__(1024) unsigned char smem[];
    const uint32_t sb = (uint32_t)__cvta_generic_to_shared(smem);
    const int tid = threadIdx.x, warp = tid >> 5, lane = tid & 31;
    const int c = blockIdx.x;
    const char* kbase = (const char*)p.k + (size_t)c * (SK * DH * 2);
    const char* vbase = (const char*)p.v + (size_t)c * (SK * DH * 2);

    const int rot = (c * ROT) & (NCH - 1);
    const char* kfirst = kbase + rot * CHUNK;
    Exchange* const gx = p.xch;

#ifdef EXIT_TEST
    if (p.first_tid == 128) return;
#endif
    uint64_t pol = 0;
    if (tid == p.first_tid) {
        PROF_AT(true, 0);
        mbar_init(sb + BAR_FULL, 1);
        asm volatile("fence.mbarrier_init.release.cluster;" ::: "memory");
        asm volatile("createpolicy.fractional.L2::evict_first.b64 %0, 1.0;" : "=l"(pol));
        mbar_expect_tx(sb + BAR_FULL, CHUNK);
        if (HEAD_BYTES) bulk_load(sb + SM_RING, kfirst, HEAD_BYTES, sb + BAR_FULL, pol);
        PROF_AT(true, 28);
    }
    if (warp == 4) {
        if (lane == 0) {
#pragma unroll
            for (int s = 0; s < NS; s++) {
                if (s) mbar_init(sb + BAR_FULL + 8 * s, 1);
                mbar_init(sb + BAR_EMPTY + 8 * s, 4);
            }
#pragma unroll
            for (int w = 0; w < 8; w++) {
                mbar_init(sb + BAR_WO + 8 * w, 1);
                mbar_init(sb + BAR_W1 + 8 * w, 1);
            }
            mbar_init(sb + BAR_DRY, 4);
            mbar_init(sb + BAR_WQ, 128);
            mbar_init(sb + BAR_Q, 1);
            mbar_init(sb + BAR_E1, 1);
            sts32(sb + SM_PROG, 0);
            sts32(sb + SM_DEPTH, 2);
            asm volatile("fence.mbarrier_init.release.cluster;" ::: "memory");
        }
        __syncthreads();
        if (lane == 0) {
            if (K0_DELAY)
                for (const long long t0 = clock64(); clock64() - t0 < K0_DELAY;) {}
            bulk_load(sb + SM_RING + HEAD_BYTES, kfirst + HEAD_BYTES, CHUNK - HEAD_BYTES, sb + BAR_FULL, pol);
            if (K1_DELAY)
                for (const long long t0 = clock64(); clock64() - t0 < K1_DELAY && !mbar_test(sb + BAR_WQ, 0);) {}
            else
                mbar_wait(sb + BAR_WQ, 0);
            int s = 1, sl = 0, landed = 0;
            uint32_t ph = 1, phl = 0;
#pragma unroll 1
            for (int i = 1; i <= 2 * NCH; i++) {
                const char* src = (i < NCH ? kbase : vbase) + ((i + rot) & (NCH - 1)) * CHUNK;
                for (int it = 0; landed < (i < 2 * NCH ? i + 1 - (int)lds32(sb + SM_DEPTH) : i); it++) {
                    if (mbar_test(sb + BAR_FULL + 8 * sl, phl) || it >= 16 * SPIN_LIMIT) {
                        PROF_AT(landed == 0, 29);
                        asm volatile("red.relaxed.gpu.global.add.u32 [%0], 1;" ::"l"(gx->count + 32) : "memory");
                        sts32(sb + SM_PROG, ++landed);
                        if (++sl == NS) { sl = 0; phl ^= 1; }
                    } else {
                        __nanosleep(20);
                    }
                }
                if (i == 2 * NCH) break;
                mbar_wait(sb + BAR_EMPTY + 8 * s, ph);
                mbar_expect_tx(sb + BAR_FULL + 8 * s, CHUNK);
                bulk_load(sb + SM_RING + s * CHUNK, src, CHUNK, sb + BAR_FULL + 8 * s, pol);
                if (++s == NS) { s = 0; ph ^= 1; }
            }
        }
    } else if (warp < 4) {
        const int g = lane >> 2, t = lane & 3, r = lane & 7, mi = lane >> 3;
        {
            uint32_t* slot = gx->q + c * 128 + tid;
            uint32_t w = 0;
            xld32(w, slot, 0);
            const int row = tid >> 2, ch = tid & 3;
            const uint32_t dst = sb + SM_WQ + row * 64 + ((ch ^ ((row >> 1) & 3)) << 4);
            const __nv_bfloat16* src = p.wq + row * (NH * DH) + c * 32 + ch * 8;
#pragma unroll
            for (int i = 0; i < 14; i++)
                asm volatile("cp.async.cg.shared.global" WQ_HINT " [%0], [%1], 16;" ::"r"(dst + i * 2048), "l"(src + i * 32 * (NH * DH)) : "memory");
            PROF_AT(tid == 0, 23);
            __syncthreads();
            asm volatile("cp.async.mbarrier.arrive.noinc.shared::cta.b64 [%0];" ::"r"(sb + BAR_WQ) : "memory");
            bar_sync(3, 256);
            w = poll32(slot, w, 0);
            xst32(slot, 0);
            sts32(sb + SM_Q + tid * 4, ~w);
        }
        bar_sync(1, 128);
        asm volatile("fence.proxy.async.shared::cta;" ::: "memory");
        if (tid == 0) mbar_arrive(sb + BAR_Q);
        PROF_AT(tid == 0, 2);
        int s = 0;
        uint32_t ph = 0;
        float rmax = -INFINITY;
        {
            uint32_t qf[32];
#pragma unroll
            for (int i = 0; i < 32; i++) qf[i] = lds32(sb + SM_Q + ((i ^ g) * 4 + t) * 4);
            uint32_t off[4];
#pragma unroll
            for (int i = 0; i < 4; i++)
                off[i] = sb + SM_RING + (warp * 16 + (mi & 1) * 8 + r) * 512 + (((2 * i + (mi >> 1)) ^ r) << 4);
            const bool owner = t == (g >> 1);
            uint32_t pdst = sb + SM_P + (t * 16 + warp * 4 + (g & 1)) * 2;
#pragma unroll 1
            for (int i = 0; i < NCH; i++) {
                mbar_wait(sb + BAR_FULL + 8 * s, ph);
                PROF_CHUNK(i);
                float acc[4][4] = {};
#pragma unroll
                for (int ks = 0; ks < 16; ks++) {
                    uint32_t a[4];
                    ldsm4(a, off[ks & 3] + s * CHUNK + (ks >> 2) * 128);
                    mma(acc[ks & 3], a, qf[2 * ks], qf[2 * ks + 1]);
                }
                __syncwarp();
                if (lane == 0) mbar_arrive(sb + BAR_EMPTY + 8 * s);
                float v[4];
#pragma unroll
                for (int e = 0; e < 4; e++) v[e] = (acc[0][e] + acc[1][e]) + (acc[2][e] + acc[3][e]);
                const float lo = (g & 1) ? v[1] : v[0], hi = (g & 1) ? v[3] : v[2];
                const uint32_t sc = pack_bf(bf_round(lo) * 0.0625f, bf_round(hi) * 0.0625f);
                if (owner) {
                    sts16(pdst, sc & 0xffffu);
                    sts16(pdst + 4, sc >> 16);
                    rmax = fmaxf(rmax, fmaxf(bf_lo(sc), bf_hi(sc)));
                }
                pdst += 128;
                if (++s == NS) { s = 0; ph ^= 1; }
            }
        }
        PROF_AT(tid == 0, 3);
        {
#pragma unroll
            for (int o = 16; o; o >>= 1) rmax = fmaxf(rmax, __shfl_xor_sync(0xffffffffu, rmax, o));
            if (lane == 0) sts32f(sb + SM_STAT + warp * 4, rmax);
            bar_sync(1, 128);
            const uint4 mx = lds128(sb + SM_STAT);
            const float m = fmaxf(fmaxf(__uint_as_float(mx.x), __uint_as_float(mx.y)),
                                  fmaxf(__uint_as_float(mx.z), __uint_as_float(mx.w)));
            float e[32];
            float sum = 0.f;
#pragma unroll
            for (int i = 0; i < 4; i++) {
                const uint4 w = lds128(sb + SM_P + (i * 128 + tid) * 16);
                const uint32_t ww[4] = {w.x, w.y, w.z, w.w};
#pragma unroll
                for (int j = 0; j < 4; j++) {
                    e[i * 8 + 2 * j] = __expf(bf_lo(ww[j]) - m);
                    e[i * 8 + 2 * j + 1] = __expf(bf_hi(ww[j]) - m);
                    sum += e[i * 8 + 2 * j] + e[i * 8 + 2 * j + 1];
                }
            }
#pragma unroll
            for (int o = 16; o; o >>= 1) sum += __shfl_xor_sync(0xffffffffu, sum, o);
            if (lane == 0) sts32f(sb + SM_STAT + 16 + warp * 4, sum);
            bar_sync(1, 128);
            const uint4 sm = lds128(sb + SM_STAT + 16);
            const float inv = 1.f / ((__uint_as_float(sm.x) + __uint_as_float(sm.y)) +
                                     (__uint_as_float(sm.z) + __uint_as_float(sm.w)));
#pragma unroll
            for (int i = 0; i < 4; i++) {
                uint4 w;
                w.x = pack_bf(e[i * 8 + 0] * inv, e[i * 8 + 1] * inv);
                w.y = pack_bf(e[i * 8 + 2] * inv, e[i * 8 + 3] * inv);
                w.z = pack_bf(e[i * 8 + 4] * inv, e[i * 8 + 5] * inv);
                w.w = pack_bf(e[i * 8 + 6] * inv, e[i * 8 + 7] * inv);
                sts128(sb + SM_P + (i * 128 + tid) * 16, w);
            }
            bar_sync(1, 128);
        }
        {
            uint32_t off[4];
#pragma unroll
            for (int i = 0; i < 4; i++)
                off[i] = sb + SM_RING + ((mi >> 1) * 8 + r) * 512 + warp * 128 + (((2 * i + (mi & 1)) ^ r) << 4);
            const uint32_t pmask = t == (g >> 1) ? ((g & 1) ? 0xffff0000u : 0x0000ffffu) : 0u;
            uint32_t* odst = gx->o + ((c & 15) * 8 + (c >> 4)) * 128 + (warp * 2 + (t >> 1)) * 16 + (g >> 1) * 4 +
                             (t & 1) * 2 + (g & 1);
            uint32_t lane2;
            asm volatile("mov.u32 %0, %%laneid;" : "=r"(lane2));
#pragma unroll 1
            for (int pass = 0; pass < 2; pass++) {
                int n = pass * NCH;
                asm volatile("" : "+r"(n));
                float acc[4][4] = {};
                uint32_t psrc = sb + SM_P + t * 32;
                uint32_t va[8][4], vb[8][4] = {};
                uint32_t pt[4] = {};
                uint32_t cur[4];
#pragma unroll
                for (int j = 0; j < 4; j++) cur[j] = off[j] + s * CHUNK;
                uint32_t bar = sb + BAR_FULL + 8 * s, ready = 0;
#pragma unroll 1
                for (int i = n; i > 0; i--) {
                    if (!ready) mbar_wait(bar, ph);
                    PROF_CHUNK(2 * NCH - i);
                    const bool wrap = bar == sb + BAR_FULL + 8 * (NS - 1);
                    const uint32_t barn = wrap ? sb + BAR_FULL : bar + 8;
                    ph ^= wrap;
                    const uint4 p0 = lds128(psrc), p1 = lds128(psrc + 16);
#pragma unroll
                    for (int j = 0; j < 2; j++) ldsm4t(va[j], cur[j & 3] + (j >> 2) * 8192);
                    uint32_t tok;
                    asm volatile("{\n.reg .pred p;\nmbarrier.test_wait.parity.shared::cta.b64 p, [%2], %3;\n"
                                 "selp.u32 %0, 1, 0, p;\nselp.u32 %1, %4, %5, p;\n}"
                                 : "=r"(ready), "=r"(tok) : "r"(barn), "r"(ph), "r"(lane), "r"(lane2) : "memory");
#pragma unroll
                    for (int j = 2; j < 8; j++) ldsm4t(va[j], cur[j & 3] + (j >> 2) * 8192);
#pragma unroll
                    for (int j = 0; j < 8; j++) mma(acc[j & 3], vb[j], pt[(j >> 2) * 2], pt[(j >> 2) * 2 + 1]);
#pragma unroll
                    for (int j = 0; j < 8; j++) ldsm4t(vb[j], cur[j & 3] + (2 + (j >> 2)) * 8192);
                    asm volatile("{\n.reg .pred p;\nsetp.eq.u32 p, %1, 0;\n@p mbarrier.arrive.shared::cta.b64 _, [%0];\n}"
                                 ::"r"(bar + 8 * NS), "r"(tok) : "memory");
                    mma(acc[0], va[0], p0.x & pmask, p0.y & pmask);
                    mma(acc[1], va[1], p0.x & pmask, p0.y & pmask);
                    mma(acc[2], va[2], p0.x & pmask, p0.y & pmask);
                    mma(acc[3], va[3], p0.x & pmask, p0.y & pmask);
                    mma(acc[0], va[4], p0.z & pmask, p0.w & pmask);
                    mma(acc[1], va[5], p0.z & pmask, p0.w & pmask);
                    mma(acc[2], va[6], p0.z & pmask, p0.w & pmask);
                    mma(acc[3], va[7], p0.z & pmask, p0.w & pmask);
                    pt[0] = p1.x & pmask;
                    pt[1] = p1.y & pmask;
                    pt[2] = p1.z & pmask;
                    pt[3] = p1.w & pmask;
                    psrc += 128;
                    bar = barn;
                    const uint32_t step = wrap ? -(NS - 1) * CHUNK : CHUNK;
#pragma unroll
                    for (int j = 0; j < 4; j++) cur[j] += step;
                }
#pragma unroll
                for (int j = 0; j < 8; j++) mma(acc[j & 3], vb[j], pt[(j >> 2) * 2], pt[(j >> 2) * 2 + 1]);
                PROF_AT(tid == 0 && pass, 4);
                float ev[4], od[4];
#pragma unroll
                for (int T = 0; T < 4; T++) {
                    ev[T] = acc[T][0] + acc[T][3];
                    od[T] = acc[T][1] + acc[T][2];
                }
                ev[0] += __shfl_xor_sync(0xffffffffu, ev[1], 1);
                od[0] += __shfl_xor_sync(0xffffffffu, od[1], 1);
                ev[2] += __shfl_xor_sync(0xffffffffu, ev[3], 1);
                od[2] += __shfl_xor_sync(0xffffffffu, od[3], 1);
                ev[0] += __shfl_xor_sync(0xffffffffu, ev[2], 2);
                od[0] += __shfl_xor_sync(0xffffffffu, od[2], 2);
                const float other = __shfl_xor_sync(0xffffffffu, (g & 1) ? ev[0] : od[0], 4);
                const uint32_t w = (g & 1) ? pack_bf(other, od[0]) : pack_bf(ev[0], other);
                xst32(odst, n ? w : EMPTY);
                PROF_AT(tid == 0 && pass, 5);
                __syncwarp();
                if (!n && lane == 0) mbar_arrive(sb + BAR_DRY);
                if (c < 112) {
                    bar_sync(1, 128);
                    if (tid == 0) {
                        const bool f1 = c < 56;
                        if (!n && (PF_EARLY & 1)) asm volatile("cp.async.bulk.prefetch.L2.global [%0], 14336;" ::"l"(p.w1 + c * 7168) : "memory");
                        if (!n && (PF_EARLY & 2)) asm volatile("cp.async.bulk.prefetch.L2.global [%0], 14336;" ::"l"(p.w2 + c * 7168) : "memory");
                        if (n) {
                            mbar_wait(sb + PF_GATE, 0);
                            if (PF_MODE & 1) asm volatile("cp.async.bulk.prefetch.L2.global [%0], 14336;" ::"l"(p.w1 + c * 7168) : "memory");
                            if ((PF_MODE & 2) && !PF_DELAY) asm volatile("cp.async.bulk.prefetch.L2.global [%0], 14336;" ::"l"(p.w2 + c * 7168) : "memory");
                            if ((PF_MODE & 2) && PF_DELAY && !f1) {
                                for (const long long t0 = clock64(); clock64() - t0 < PF_DELAY;) {}
                                asm volatile("cp.async.bulk.prefetch.L2.global [%0], 28672;" ::"l"(p.w2 + (c - 56) * 14336) : "memory");
                            }
                            mbar_wait(sb + (f1 ? W1_GATE : W2_GATE), 0);
                            for (const long long t0 = clock64(); clock64() - t0 < (f1 ? W1_DELAY : W2_DELAY);) {}
                        }
                        if (NO_W & (f1 ? 1 : 2)) {
                            for (int i = 0; n && i < 8; i++) mbar_arrive(sb + BAR_W1 + 8 * i);
                        } else if ((NO_W & 4) && !f1) {
                            tile_loads(sb + SM_WX, &p.map_w2, ((c - 56) % 28) * 16, 0, 224, 7168, sb + BAR_W1, n ? 4 : 0);
                            for (int i = 4; n && i < 8; i++) mbar_arrive(sb + BAR_W1 + 8 * i);
                        } else if ((NO_W & 8) && !f1) {
                            for (int i = 0; n && i < 8; i++) mbar_arrive(sb + BAR_W1 + 8 * i);
                            tile_loads(sb + SM_WX, &p.map_w2, ((c - 56) % 28) * 16, 0, 224, 7168, sb + BAR_WO, n ? 8 : 0);
                            if (n) mbar_wait(sb + BAR_WO + 56, 1);
                        } else
                        tile_loads(sb + SM_WX, f1 ? &p.map_w1 : &p.map_w2, f1 ? c * 32 : ((c - 56) % 28) * 16, 0, f1 ? 64 : 224,
                                   f1 ? 4096 : 7168, sb + BAR_W1, n ? 8 - f1 : 0);
                    }
                }
            }
        }
    } else {
        const int ew = warp - 5, et = tid - 160;
        const int r = lane & 7, mi = lane >> 3;
        {
            uint32_t w[7];
#pragma unroll
            for (int i = 0; i < 7; i++)
                asm volatile("ld.global.nc.u32 %0, [%1];" : "=r"(w[i]) : "l"((const uint32_t*)p.x + ew * 224 + i * 32 + lane));
            __syncthreads();
            PROF_AT(et == 0, 24);
            PROF_AT(et == 0 && w[0] + w[6] != 0x12345, 25);
            layernorm_row(w, sb + SM_XN + ew * 912, lane);
            PROF_AT(et == 0, 26);
            mbar_wait(sb + BAR_WQ, 0);
            PROF_AT(et == 0, 27);
            uint32_t a[8][4];
            frags_w448(a, sb + SM_WQ, ew, lane);
            const float2 q = gemv448(a, sb, ew, lane, et);
            if (et < 128) {
                xst32(gx->q + ((et >> 4) * 16 + (c >> 3)) * 128 + (c & 7) * 16 + (et & 15), ~pack_bf(q.x, q.y));
                asm volatile("bar.arrive 3, 256;" ::: "memory");
            }
            PROF_AT(et == 0, 1);
        }
        const int hh = c / 7, jj = c - hh * 7;
        const bool is_f1 = c < 56;
        const int cg = (c - 56) % 28, half = (c - 56) / 28;
        const int hk = c - 112, hb = (ew >> 1) * 2 + (mi & 1);
        uint32_t side = 0;
        if (c < 126)
            asm volatile("ld.global.nc.u32 %0, [%1];" : "=r"(side)
                         : "l"(is_f1 ? p.b1 + c * 32 + (et & 15) * 2
                                     : c < 112 ? p.b2 + cg * 16 + r * 2 : p.x + hb * DM + hk * 32 + (r & 3) * 8 + (ew & 1) * 4 + (r >> 2) * 2));
        uint32_t seen_prog = 0;
#pragma unroll 1
        for (int pass = 0; pass < 2; pass++) {
            uint32_t live = pass;
            asm volatile("" : "+r"(live));
            const uint32_t want = 0u - live, wipe = ~want;
            const int et = pin(tid - 160), ew = et >> 5, lane = et & 31;
            const int g = lane >> 2, t = lane & 3, r = lane & 7, mi = lane >> 3;
            if (et == 0) {
                if (!live) mbar_wait(sb + BAR_Q, 0);
#pragma unroll 1
                for (int it = 0; it < SPIN_LIMIT; it++) {
                    const uint32_t prog = lds32(sb + SM_PROG);
                    int total = 0;
                    if (prog == seen_prog) __nanosleep(MON_SLEEP);
                    if (prog != seen_prog || prog >= 2 * NCH - 8)
                        asm volatile("ld.relaxed.gpu.global.u32 %0, [%1];" : "=r"(total) : "l"(gx->count + 32) : "memory");
                    if (total >= ALL_CHUNKS - LIFT_LEFT) {
                        sts32(sb + SM_DEPTH, NS);
                    } else if (prog != seen_prog) {
                        const int lead = prog * NCTA - total;
                        sts32(sb + SM_DEPTH, lead >= LEAD1 ? 1 : lead >= LEAD2 ? 2 : lead >= LEAD2 - LSTEP ? 3 : lead >= LEAD2 - 2 * LSTEP ? 4 : NS);
                    }
                    seen_prog = prog;
                    if (live ? total >= ALL_CHUNKS - TRIG_LEFT || (c >= 126 && prog == 2 * NCH) : mbar_test(sb + BAR_DRY, 0)) break;
                }
                tile_loads(sb + SM_WO, &p.map_wo, jj * 64, hh * 256, 32, 4096, sb + BAR_WO, live && c < 112 ? 8 : 0);
                if (!live) {
                    asm volatile("prefetch.tensormap [%0];" ::"l"(&p.map_wo) : "memory");
                    asm volatile("prefetch.tensormap [%0];" ::"l"(is_f1 ? &p.map_w1 : &p.map_w2) : "memory");
                }
            } else if (et == 32 && live) {
                uint32_t seen;
                mbar_wait(sb + BAR_DRY, 0);
                asm volatile("atom.release.gpu.global.add.u32 %0, [%1], 1;" : "=r"(seen) : "l"(gx->count) : "memory");
                int it = 0;
                for (seen++; c < 126 && seen < NCTA && ++it < SPIN_LIMIT;) {
                    __nanosleep(512);
                    asm volatile("ld.relaxed.gpu.global.u32 %0, [%1];" : "=r"(seen) : "l"(gx->count) : "memory");
                }
                asm volatile("ld.acquire.gpu.global.u32 %0, [%1];" : "=r"(seen) : "l"(gx->count) : "memory");
                PROF_AT(true, 22);
            }
            __syncwarp();
            if (c >= 126) continue;
            bar_sync(2, 256);
            PROF_AT(et == 0, live ? 6 : 18);
            if (c >= 112) {
                const bool odd = mi & 1;
                const int hb = (ew >> 1) * 2 + (mi & 1);
                float a0, a1;
                uint32_t* const dst = gx->h + pin((((mi >> 1) * 14 + hk) * 8 + hb) * 16 + (ew & 1) * 8 + r);
                uint4 v[4] = {};
                const uint32_t* psrc = gx->part + pin((hk * 8 + ew) * 512 + lane * 4);
                const auto head = [&](const uint4 (&v)[4]) {
                    const float f0 = (__uint_as_float(v[0].x) + __uint_as_float(v[1].x)) + (__uint_as_float(v[2].x) + __uint_as_float(v[3].x));
                    const float f1 = (__uint_as_float(v[0].y) + __uint_as_float(v[1].y)) + (__uint_as_float(v[2].y) + __uint_as_float(v[3].y));
                    const float f2 = (__uint_as_float(v[0].z) + __uint_as_float(v[1].z)) + (__uint_as_float(v[2].z) + __uint_as_float(v[3].z));
                    const float f3 = (__uint_as_float(v[0].w) + __uint_as_float(v[1].w)) + (__uint_as_float(v[2].w) + __uint_as_float(v[3].w));
                    a0 = (odd ? f1 : f0) + __shfl_xor_sync(0xffffffffu, odd ? f0 : f1, 8);
                    a1 = (odd ? f3 : f2) + __shfl_xor_sync(0xffffffffu, odd ? f2 : f3, 8);
                };
                poll128<4, 128>(v, psrc, want, want, head);
                a0 += __shfl_xor_sync(0xffffffffu, a0, 16);
                a1 += __shfl_xor_sync(0xffffffffu, a1, 16);
                xst32(dst, bf2_add(side, pack_bf(a0, a1)) | wipe);
                PROF_AT(et == 0 && live, 9);
                if (!live) bar_sync(2, 256);
                continue;
            }
            {
                uint32_t fa[4];
#pragma unroll
                for (int mt = 0; mt < 4; mt++)
                    fa[mt] = pin(sb + SM_WO + (ew * 32 + (mi >> 1) * 8 + r) * 128 + (((2 * mt + (mi & 1)) ^ r) << 4));
                const uint32_t wb = pin(sb + SM_RED + (ew * 544 + t * 136 + g * 2) * 4);
                const uint32_t rb = pin(sb + SM_RED + ((ew & 3) * 136 + ((ew >> 2) * 32 + (r >> 1) * 8 + mi * 2 + (r & 1)) * 2) * 4);
                const uint32_t* osrc = gx->o + pin((hh * 8 + g) * 128 + ew * 16 + t * 4);
                uint32_t* const pdst = gx->part + pin((((jj * 8 + ew) * 2 + (lane >> 4)) * 16 + hh) * 32 + (lane & 15) * 2);
                const uint32_t gate = sb + (live ? BAR_WO + 8 * ew : BAR_DRY);
                uint4 o = make_uint4(want, want, want, want);
                uint32_t top = want;
                int left = SPIN_LIMIT;
                bool pending;
#pragma unroll 1
                do {
                    xld128(o, osrc, top);
                    top = top_word(o);
                    left--;
                    pending = __any_sync(0xffffffffu, top == EMPTY && left > 0);
                } while (pending && !mbar_test(gate, 0));
                mbar_wait(gate, 0);
                PROF_AT(et == 0 && live, 7);
                uint32_t a[8][4];
#pragma unroll
                for (int mt = 0; mt < 4; mt++) ldsm4t(a[mt], fa[mt]);
#pragma unroll
                for (int mt = 0; mt < 4; mt++) ldsm4t(a[4 + mt], fa[mt] + 2048);
                float acc[4][4];
#pragma unroll 1
                do {
                    xld128(o, osrc, top);
                    top = top_word(o);
                    left--;
                    pending = __any_sync(0xffffffffu, top == EMPTY && left > 0);
#pragma unroll
                    for (int mt = 0; mt < 4; mt++) mma0(acc[mt], a[mt], o.x, o.y);
#pragma unroll
                    for (int mt = 0; mt < 4; mt++) mma(acc[mt], a[4 + mt], o.z, o.w);
                } while (pending);
                PROF_AT(et == 0 && live, 8);
#pragma unroll
                for (int mt = 0; mt < 4; mt++) {
                    sts64f(wb + mt * 128, acc[mt][0], acc[mt][1]);
                    sts64f(wb + mt * 128 + 64, acc[mt][2], acc[mt][3]);
                }
                bar_sync(2, 256);
                float2 v[8];
#pragma unroll
                for (int w = 0; w < 8; w++) v[w] = lds64f(rb + w * 2176);
                const float s0 = ((v[0].x + v[1].x) + (v[2].x + v[3].x)) + ((v[4].x + v[5].x) + (v[6].x + v[7].x));
                const float s1 = ((v[0].y + v[1].y) + (v[2].y + v[3].y)) + ((v[4].y + v[5].y) + (v[6].y + v[7].y));
                xst64(pdst, __float_as_uint(s0) | wipe, __float_as_uint(s1) | wipe);
            }
            if (et == 0 && live) mbar_arrive(sb + BAR_E1);
            PROF_AT(et == 0 && live, 13);
            if (!is_f1 || ew < 7) mbar_wait(sb + (live ? BAR_W1 + 8 * ew : BAR_DRY), 0);
            PROF_AT(et == 192 && live, 15);
            if (is_f1) {
                constexpr uint32_t ONES = 0x3f803f80u;
                if (ew < 7) {
                    uint32_t a[8][4];
                    frags_w448(a, sb + SM_WX, ew, lane);
                    float cs[2][4] = {};
#pragma unroll
                    for (int ks = 0; ks < 4; ks++) {
                        mma(cs[0], a[ks * 2], ONES, ONES);
                        mma(cs[1], a[ks * 2 + 1], ONES, ONES);
                    }
                    if (t == 0) {
                        const uint32_t cb = sb + SM_XN + (ew * 32 + g) * 4;
                        sts32f(cb, cs[0][0]);
                        sts32f(cb + 32, cs[0][2]);
                        sts32f(cb + 64, cs[1][0]);
                        sts32f(cb + 96, cs[1][2]);
                    }
                    bar_sync(4, 224);
                    float2 colsum = make_float2(0.f, 0.f);
#pragma unroll
                    for (int w = 0; w < 7; w++) {
                        const float2 x = lds64f(sb + SM_XN + (w * 32 + (et & 15) * 2) * 4);
                        colsum.x += x.x;
                        colsum.y += x.y;
                    }
                    const int b = (et >> 4) & 7, pr = et & 15;
                    const uint32_t wb = pin(sb + SM_RED + (ew * 288 + t * 72 + g) * 4);
                    const uint32_t sw = pin(sb + SM_RED + (ew * 288 + g * 36 + (t == (g >> 1) ? 32 : 34)) * 4);
                    const uint32_t rs = pin(sb + SM_RED + b * 144 + 128), rz = pin(sb + SM_RED + b * 144 + pr * 8);
                    const bool odd = pin(g & 1);
                    uint32_t* const dst = gx->r + pin((((b >> 2) * 56 + c) * 4 + (b & 3)) * 16 + (pr & 3) * 4 + (pr >> 2));
                    float z[2][4], st[4];
                    uint4 v[2] = {};
                    const auto step = [&](int ks, const uint4& x) {
                        const uint32_t b0 = (ks & 1) ? x.z : x.x, b1 = (ks & 1) ? x.w : x.y;
                        const uint32_t sa[4] = {b0, ONES, b1, ONES};
                        if (ks == 0) {
                            mma0(st, sa, b0, b1);
                            mma0(z[0], a[0], b0, b1);
                            mma0(z[1], a[1], b0, b1);
                        } else {
                            mma(st, sa, b0, b1);
                            mma(z[0], a[ks * 2], b0, b1);
                            mma(z[1], a[ks * 2 + 1], b0, b1);
                        }
                    };
                    poll128<2, 128>(v, gx->h + pin(((c & 1) * 14 + ew * 2) * 128 + lane * 4), want, want, [&](const uint4 (&x)[2]) {
                        step(0, x[0]);
                        step(1, x[0]);
                    });
                    step(2, v[1]);
                    step(3, v[1]);
                    PROF_AT(et == 0 && live, 10);
                    sts64f(sw, odd ? st[3] : st[2], odd ? st[1] : st[0]);
#pragma unroll
                    for (int mt = 0; mt < 2; mt++) {
                        sts32f(wb + mt * 64, z[mt][0]);
                        sts32f(wb + mt * 64 + 144, z[mt][1]);
                        sts32f(wb + mt * 64 + 32, z[mt][2]);
                        sts32f(wb + mt * 64 + 176, z[mt][3]);
                    }
                    bar_sync(4, 224);
                    if (ew < 4) {
                        float2 sv[7], zv[7];
#pragma unroll
                        for (int w = 0; w < 7; w++) sv[w] = lds64f(rs + w * 1152);
#pragma unroll
                        for (int w = 0; w < 7; w++) zv[w] = lds64f(rz + w * 1152);
                        const float mu = (((sv[0].x + sv[1].x) + (sv[2].x + sv[3].x)) + ((sv[4].x + sv[5].x) + sv[6].x)) * (1.f / DM);
                        const float sq = ((sv[0].y + sv[1].y) + (sv[2].y + sv[3].y)) + ((sv[4].y + sv[5].y) + sv[6].y);
                        const float inv = inv_std(bf_round(fmaxf(fmaf(sq, 1.f / DM, -mu * mu), 0.f)));
                        const float mean = bf_round(mu);
                        const float z0 = ((zv[0].x + zv[1].x) + (zv[2].x + zv[3].x)) + ((zv[4].x + zv[5].x) + zv[6].x);
                        const float z1 = ((zv[0].y + zv[1].y) + (zv[2].y + zv[3].y)) + ((zv[4].y + zv[5].y) + zv[6].y);
                        const uint32_t u = pack_bf(fmaf(-mean, colsum.x, z0) * inv, fmaf(-mean, colsum.y, z1) * inv);
                        xst32(dst, bf2_relu_sq(bf2_add(u, side)) | wipe);
                    }
                    PROF_AT(et == 0 && live, 11);
                }
            } else {
                uint32_t a[14][4];
                const uint32_t base = sb + SM_WX + (ew * 224 + (mi >> 1) * 8 + r) * 32 + (((mi & 1) ^ (r >> 2)) << 4);
#pragma unroll
                for (int ks = 0; ks < 14; ks++) ldsm4t(a[ks], base + ks * 512);
                const uint32_t wb = pin(sb + SM_XN + (ew * 160 + (t & 1) * 80 + (g >> 1) * 4 + (t >> 1) * 2 + (g & 1)) * 4);
                const uint32_t rb = pin(sb + SM_XN + (mi * 40 + r * 4) * 4);
                const bool upper = pin(t >> 1);
                uint32_t* const dst = (live ? (uint32_t*)p.out : gx->sink) + pin((half * 4 + mi) * 224 + cg * 8 + r);
                const uint32_t* rsrc = gx->r + pin((half * 56 + ew * 7) * 64 + lane * 4);
                const uint32_t* hsrc = gx->h + pin((((c & 1) * 14 + (cg >> 1)) * 8 + half * 4 + mi) * 16 + (r & 3) * 4 +
                                                   (cg & 1) * 2 + (r >> 2));
                uint32_t hres = ew == 0 ? want : 0u;
                PROF_AT(et == 0 && live, 16);
                float acc[4][4];
                uint4 v[4] = {};
                const auto step = [&](int i) {
                    mma(acc[0], a[4 * i], v[i].x, v[i].y);
                    mma(acc[1], a[4 * i + 1], v[i].z, v[i].w);
                    if (i < 3) {
                        mma(acc[2], a[4 * i + 2], v[i].x, v[i].y);
                        mma(acc[3], a[4 * i + 3], v[i].z, v[i].w);
                    }
                };
                poll128<4, 128>(v, rsrc, want, lane < 16 ? want : 0u, [&](const uint4 (&)[4]) {
                    mma0(acc[0], a[0], v[0].x, v[0].y);
                    mma0(acc[1], a[1], v[0].z, v[0].w);
                    mma0(acc[2], a[2], v[0].x, v[0].y);
                    mma0(acc[3], a[3], v[0].z, v[0].w);
                    step(1);
                }, hsrc, &hres);
                step(2);
                step(3);
                PROF_AT(et == 0 && live, 17);
                sts32f(wb, upper ? acc[2][0] + acc[3][0] : acc[0][0] + acc[1][0]);
                sts32f(wb + 160, upper ? acc[2][1] + acc[3][1] : acc[0][1] + acc[1][1]);
                sts32f(wb + 64, upper ? acc[2][2] + acc[3][2] : acc[0][2] + acc[1][2]);
                sts32f(wb + 224, upper ? acc[2][3] + acc[3][3] : acc[0][3] + acc[1][3]);
                if (ew == 0) {
                    bar_sync(2, 256);
                    float x[8], y[8];
#pragma unroll
                    for (int w = 0; w < 8; w++) {
                        const uint4 q = lds128(rb + w * 640);
                        x[w] = __uint_as_float(q.x) + __uint_as_float(q.z);
                        y[w] = __uint_as_float(q.y) + __uint_as_float(q.w);
                    }
                    const float s0 = ((x[0] + x[1]) + (x[2] + x[3])) + ((x[4] + x[5]) + (x[6] + x[7]));
                    const float s1 = ((y[0] + y[1]) + (y[2] + y[3])) + ((y[4] + y[5]) + (y[6] + y[7]));
                    *dst = bf2_add(hres, bf2_add(pack_bf(s0, s1), side));
                    PROF_AT(et == 0 && live, 12);
                } else {
                    asm volatile("bar.arrive 2, 256;" ::: "memory");
                    if (c == 56 && et == 32 && live) {
                        xst32(gx->count, 0);
                        xst32(gx->count + 32, 0);
                    }
                }
            }
            if (!live) bar_sync(5, 256);
            PROF_AT(et == 0 && !live, 19);
        }
    }
}

using EncodeFn = CUresult (*)(CUtensorMap*, CUtensorMapDataType, cuuint32_t, void*, const cuuint64_t*, const cuuint64_t*,
                              const cuuint32_t*, const cuuint32_t*, CUtensorMapInterleave, CUtensorMapSwizzle,
                              CUtensorMapL2promotion, CUtensorMapFloatOOBfill);

void encode_map(EncodeFn fn, CUtensorMap* map, const void* base, int rows, int cols, int box_rows, int box_cols,
                CUtensorMapSwizzle swizzle) {
    const cuuint64_t dims[2] = {(cuuint64_t)cols, (cuuint64_t)rows};
    const cuuint64_t strides[1] = {(cuuint64_t)cols * 2};
    const cuuint32_t box[2] = {(cuuint32_t)box_cols, (cuuint32_t)box_rows};
    const cuuint32_t steps[2] = {1, 1};
    fn(map, CU_TENSOR_MAP_DATA_TYPE_BFLOAT16, 2, const_cast<void*>(base), dims, strides, box, steps,
       CU_TENSOR_MAP_INTERLEAVE_NONE, swizzle, L2PROMO, CU_TENSOR_MAP_FLOAT_OOB_FILL_NONE);
}

}

extern "C" void kernel_launch(void* const* d_in, const int* in_sizes, int n_in, void* d_out, int out_size) {
    (void)in_sizes; (void)n_in; (void)out_size;
    Params p;
    p.first_tid = 128;
    p.x = (const __nv_bfloat16*)d_in[0];
    p.k = (const __nv_bfloat16*)d_in[1];
    p.v = (const __nv_bfloat16*)d_in[2];
    p.wq = (const __nv_bfloat16*)d_in[3];
    p.wo = (const __nv_bfloat16*)d_in[4];
    p.w1 = (const __nv_bfloat16*)d_in[6];
    p.b1 = (const __nv_bfloat16*)d_in[7];
    p.w2 = (const __nv_bfloat16*)d_in[8];
    p.b2 = (const __nv_bfloat16*)d_in[9];
    p.out = (__nv_bfloat16*)d_out;
    cudaGetSymbolAddress((void**)&p.xch, g_x);
    void* fn = nullptr;
    cudaDriverEntryPointQueryResult found;
    cudaGetDriverEntryPoint("cuTensorMapEncodeTiled", &fn, cudaEnableDefault, &found);
    encode_map((EncodeFn)fn, &p.map_wo, p.wo, NH * DH, DM, 32, 64, CU_TENSOR_MAP_SWIZZLE_128B);
    encode_map((EncodeFn)fn, &p.map_w1, p.w1, DM, FF, 64, 32, CU_TENSOR_MAP_SWIZZLE_64B);
    encode_map((EncodeFn)fn, &p.map_w2, p.w2, FF, DM, 224, 16, CU_TENSOR_MAP_SWIZZLE_32B);
    cudaFuncSetAttribute(fused_decode_kernel, cudaFuncAttributeMaxDynamicSharedMemorySize, SM_TOTAL);
    fused_decode_kernel<<<NCTA, NTHREADS, SM_TOTAL>>>(p);
}
```

```cpp
#include <cuda.h>
#include <cuda_runtime.h>
#include <cuda_bf16.h>
#include <stdint.h>

namespace {

constexpr int DM = 448, NH = 16, SK = 4096, DH = 256, FF = 1792;
constexpr int NCTA = 128;
constexpr int CHUNK = 32768;
constexpr int NCH = SK / 64;
constexpr int NS = 5;
constexpr int ALL_CHUNKS = NCTA * 2 * NCH;
constexpr int LEAD1 = 256;
constexpr int LEAD2 = -128;
constexpr int LIFT_LEFT = 350;
constexpr int TRIG_LEFT = 220;
constexpr int K1_DELAY = 2000;
constexpr int W1_DELAY = 600;
constexpr int PF_DELAY = 500;
constexpr int W2_DELAY = 600;
constexpr int ROT = 32;
constexpr int NTHREADS = 13 * 32;
constexpr int SPIN_LIMIT = 1 << 20;

constexpr int SM_RING = 0;
constexpr int SM_WX = 0;
constexpr int SM_WQ = NS * CHUNK;
constexpr int SM_WO = SM_WQ;
constexpr int SM_P = SM_WQ + 32768;
constexpr int SM_RED = SM_P + 8192;
constexpr int SM_XN = SM_RED + 8 * 544 * 4;
constexpr int SM_Q = SM_XN + 8 * 456 * 2;
constexpr int SM_STAT = SM_Q + 512;
constexpr int SM_PROG = SM_STAT + 32, SM_DEPTH = SM_STAT + 36;
constexpr int SM_BAR = SM_STAT + 64;
constexpr int BAR_FULL = SM_BAR, BAR_EMPTY = BAR_FULL + 8 * NS, BAR_WO = BAR_EMPTY + 8 * NS, BAR_DRY = BAR_WO + 64,
              BAR_WQ = BAR_DRY + 8, BAR_Q = BAR_WQ + 8, BAR_W0 = BAR_WO + 56, BAR_E1 = BAR_Q + 8, BAR_X = BAR_E1 + 8,
              BAR_W1 = BAR_X + 16;
constexpr int SM_TOTAL = BAR_W1 + 64;
static_assert(SM_TOTAL <= 232448, "shared memory budget");

struct Exchange {
    uint32_t q[NCTA * 128];
    uint32_t o[NH * 8 * 128];
    uint32_t part[14 * 8 * 16 * 32];
    uint32_t h[2 * 14 * 8 * 16];
    uint32_t r[2 * 56 * 4 * 16];
    uint32_t count[64];
    uint32_t sink[8 * 224];
};
__device__ __align__(128) Exchange g_x;

__device__ __forceinline__ void mbar_init(uint32_t bar, uint32_t count) {
    asm volatile("mbarrier.init.shared::cta.b64 [%0], %1;" ::"r"(bar), "r"(count) : "memory");
}
__device__ __forceinline__ void mbar_arrive(uint32_t bar) {
    asm volatile("mbarrier.arrive.shared::cta.b64 _, [%0];" ::"r"(bar) : "memory");
}
__device__ __forceinline__ void mbar_expect_tx(uint32_t bar, uint32_t bytes) {
    asm volatile("mbarrier.arrive.expect_tx.shared::cta.b64 _, [%0], %1;" ::"r"(bar), "r"(bytes) : "memory");
}
__device__ __forceinline__ void mbar_wait(uint32_t bar, uint32_t parity) {
    uint32_t done;
    int it = 0;
    do {
        asm volatile("{\n.reg .pred p;\nmbarrier.try_wait.parity.shared::cta.b64 p, [%1], %2;\nselp.u32 %0, 1, 0, p;\n}"
                     : "=r"(done) : "r"(bar), "r"(parity) : "memory");
    } while (!done && ++it < SPIN_LIMIT);
}
__device__ __forceinline__ uint32_t mbar_test(uint32_t bar, uint32_t parity) {
    uint32_t done;
    asm volatile("{\n.reg .pred p;\nmbarrier.test_wait.parity.shared::cta.b64 p, [%1], %2;\nselp.u32 %0, 1, 0, p;\n}"
                 : "=r"(done) : "r"(bar), "r"(parity) : "memory");
    return done;
}
__device__ __forceinline__ void spin(uint32_t cycles) {
    const uint32_t t0 = (uint32_t)clock();
    do {
    } while ((uint32_t)clock() - t0 < cycles);
}
__device__ __forceinline__ void spin_or(uint32_t cycles, uint32_t bar) {
    const uint32_t t0 = (uint32_t)clock();
    do {
    } while (!mbar_test(bar, 0) && (uint32_t)clock() - t0 < cycles);
}
__device__ __forceinline__ void l2_prefetch(const void* src, uint32_t bytes, uint32_t on) {
    asm volatile("{\n.reg .pred p;\nsetp.ne.u32 p, %2, 0;\n@p cp.async.bulk.prefetch.L2.global [%0], %1;\n}"
                 ::"l"(src), "r"(bytes), "r"(on) : "memory");
}
__device__ __forceinline__ void bulk_load(uint32_t dst, const void* src, uint32_t bytes, uint32_t bar, uint64_t pol) {
    asm volatile("cp.async.bulk.shared::cluster.global.mbarrier::complete_tx::bytes.L2::cache_hint [%0], [%1], %2, [%3], %4;"
                 ::"r"(dst), "l"(src), "r"(bytes), "r"(bar), "l"(pol) : "memory");
}
__device__ __forceinline__ void tile_loads(uint32_t dst, const CUtensorMap* map, int col, int row, int rows, uint32_t bytes,
                                           uint32_t bar, int n) {
#pragma unroll 1
    for (int i = 0; i < n; i++, dst += bytes, row += rows, bar += 8) {
        mbar_expect_tx(bar, bytes);
        asm volatile("cp.async.bulk.tensor.2d.shared::cluster.global.mbarrier::complete_tx::bytes [%0], [%1, {%2, %3}], [%4];"
                     ::"r"(dst), "l"(map), "r"(col), "r"(row), "r"(bar) : "memory");
    }
}
__device__ __forceinline__ void bar_sync(int id, int n) { asm volatile("bar.sync %0, %1;" ::"r"(id), "r"(n) : "memory"); }

__device__ __forceinline__ void ldsm4(uint32_t (&r)[4], uint32_t a) {
    asm volatile("ldmatrix.sync.aligned.m8n8.x4.shared.b16 {%0,%1,%2,%3}, [%4];"
                 : "=r"(r[0]), "=r"(r[1]), "=r"(r[2]), "=r"(r[3]) : "r"(a) : "memory");
}
__device__ __forceinline__ void ldsm4t(uint32_t (&r)[4], uint32_t a) {
    asm volatile("ldmatrix.sync.aligned.m8n8.x4.trans.shared.b16 {%0,%1,%2,%3}, [%4];"
                 : "=r"(r[0]), "=r"(r[1]), "=r"(r[2]), "=r"(r[3]) : "r"(a) : "memory");
}
__device__ __forceinline__ void mma(float (&c)[4], const uint32_t (&a)[4], uint32_t b0, uint32_t b1) {
    asm volatile("mma.sync.aligned.m16n8k16.row.col.f32.bf16.bf16.f32 {%0,%1,%2,%3}, {%4,%5,%6,%7}, {%8,%9}, {%0,%1,%2,%3};"
                 : "+f"(c[0]), "+f"(c[1]), "+f"(c[2]), "+f"(c[3])
                 : "r"(a[0]), "r"(a[1]), "r"(a[2]), "r"(a[3]), "r"(b0), "r"(b1));
}
__device__ __forceinline__ void mma0(float (&c)[4], const uint32_t (&a)[4], uint32_t b0, uint32_t b1) {
    asm volatile("mma.sync.aligned.m16n8k16.row.col.f32.bf16.bf16.f32 {%0,%1,%2,%3}, {%4,%5,%6,%7}, {%8,%9}, {%10,%10,%10,%10};"
                 : "=f"(c[0]), "=f"(c[1]), "=f"(c[2]), "=f"(c[3])
                 : "r"(a[0]), "r"(a[1]), "r"(a[2]), "r"(a[3]), "r"(b0), "r"(b1), "f"(0.f));
}
__device__ __forceinline__ uint32_t lds32(uint32_t a) {
    uint32_t v;
    asm volatile("ld.shared.u32 %0, [%1];" : "=r"(v) : "r"(a) : "memory");
    return v;
}
__device__ __forceinline__ uint32_t ctl_load(uint32_t a) {
    uint32_t v;
    asm volatile("ld.volatile.shared.u32 %0, [%1];" : "=r"(v) : "r"(a) : "memory");
    return v;
}
__device__ __forceinline__ void ctl_store(uint32_t a, uint32_t v) {
    asm volatile("st.volatile.shared.u32 [%0], %1;" ::"r"(a), "r"(v) : "memory");
}
__device__ __forceinline__ float2 lds64f(uint32_t a) {
    float2 v;
    asm volatile("ld.shared.v2.f32 {%0,%1}, [%2];" : "=f"(v.x), "=f"(v.y) : "r"(a) : "memory");
    return v;
}
__device__ __forceinline__ uint4 lds128(uint32_t a) {
    uint4 v;
    asm volatile("ld.shared.v4.u32 {%0,%1,%2,%3}, [%4];" : "=r"(v.x), "=r"(v.y), "=r"(v.z), "=r"(v.w) : "r"(a) : "memory");
    return v;
}
__device__ __forceinline__ void sts16(uint32_t a, uint32_t v) {
    asm volatile("st.shared.u16 [%0], %1;" ::"r"(a), "h"((unsigned short)v) : "memory");
}
__device__ __forceinline__ void sts32(uint32_t a, uint32_t v) {
    asm volatile("st.shared.u32 [%0], %1;" ::"r"(a), "r"(v) : "memory");
}
__device__ __forceinline__ void sts32f(uint32_t a, float v) {
    asm volatile("st.shared.f32 [%0], %1;" ::"r"(a), "f"(v) : "memory");
}
__device__ __forceinline__ void sts64f(uint32_t a, float x, float y) {
    asm volatile("st.shared.v2.f32 [%0], {%1,%2};" ::"r"(a), "f"(x), "f"(y) : "memory");
}
__device__ __forceinline__ void sts128(uint32_t a, uint4 v) {
    asm volatile("st.shared.v4.u32 [%0], {%1,%2,%3,%4};" ::"r"(a), "r"(v.x), "r"(v.y), "r"(v.z), "r"(v.w) : "memory");
}

constexpr uint32_t EMPTY = 0xffffffffu;
__device__ __forceinline__ void xld32(uint32_t& v, const uint32_t* p, uint32_t empty) {
    asm volatile("{\n.reg .pred p;\nsetp.eq.u32 p, %0, %2;\n@p ld.relaxed.gpu.global.u32 %0, [%1];\n}"
                 : "+r"(v) : "l"(p), "r"(empty) : "memory");
}
__device__ __forceinline__ void xld128(uint4& v, const uint32_t* p, uint32_t top) {
    asm volatile("{\n.reg .pred p;\nsetp.eq.u32 p, %5, 0xffffffff;\n@p ld.relaxed.gpu.global.v4.u32 {%0,%1,%2,%3}, [%4];\n}"
                 : "+r"(v.x), "+r"(v.y), "+r"(v.z), "+r"(v.w) : "l"(p), "r"(top) : "memory");
}
__device__ __forceinline__ void xst32(uint32_t* p, uint32_t v) {
    asm volatile("st.relaxed.gpu.global.u32 [%0], %1;" ::"l"(p), "r"(v) : "memory");
}
__device__ __forceinline__ void xst64(uint32_t* p, uint32_t a, uint32_t b) {
    asm volatile("st.relaxed.gpu.global.v2.u32 [%0], {%1,%2};" ::"l"(p), "r"(a), "r"(b) : "memory");
}
__device__ __forceinline__ uint32_t top_word(const uint4& v) { return max(__vimax3_u32(v.x, v.y, v.z), v.w); }
template <int N, int STRIDE, bool WORD = false>
struct Poll {
    uint4 v[N];
    uint32_t top[N], word, want;
    const uint32_t *src, *wsrc;
    int left;
    __device__ __forceinline__ Poll(const uint32_t* s, uint32_t init, uint32_t init_last, const uint32_t* ws = nullptr,
                                    uint32_t init_word = 0)
        : word(init_word), want(init), src(s), wsrc(ws), left(init ? SPIN_LIMIT : 2) {
#pragma unroll
        for (int i = 0; i < N; i++) {
            top[i] = i == N - 1 ? init_last : init;
            v[i] = make_uint4(top[i], top[i], top[i], top[i]);
        }
    }
    __device__ __forceinline__ void issue() {
#pragma unroll
        for (int i = 0; i < N; i++) xld128(v[i], src + i * STRIDE, top[i]);
        if (WORD) xld32(word, wsrc, EMPTY);
        left--;
    }
    __device__ __forceinline__ bool missing() {
        uint32_t m = WORD ? word : 0;
#pragma unroll
        for (int i = 0; i < N; i++) {
            top[i] = top_word(v[i]);
            m = max(m, top[i]);
        }
        return __any_sync(0xffffffffu, m == want && left > 0);
    }
    __device__ __forceinline__ void until(uint32_t bar) {
#pragma unroll 1
        while (!mbar_test(bar, 0)) {
            issue();
            if (!missing()) break;
        }
        mbar_wait(bar, ~want & 1);
    }
    template <class F>
    __device__ __forceinline__ void finish(F use) {
        bool again;
#pragma unroll 1
        do {
            issue();
            again = missing();
            use();
        } while (again);
    }
};
__device__ __forceinline__ uint32_t poll32(const uint32_t* src, uint32_t init, uint32_t empty) {
    int left = SPIN_LIMIT;
#pragma unroll 1
    do {
        xld32(init, src, empty);
        left--;
    } while (__any_sync(0xffffffffu, init == empty && left > 0));
    return init;
}
__device__ __forceinline__ uint32_t pin(uint32_t v) {
    asm volatile("shfl.sync.bfly.b32 %0, %0, 0, 0x1f, 0xffffffff;" : "+r"(v));
    return v;
}
__device__ __forceinline__ uint32_t bf2_add(uint32_t a, uint32_t b) {
    uint32_t r;
    asm("add.rn.bf16x2 %0, %1, %2;" : "=r"(r) : "r"(a), "r"(b));
    return r;
}
__device__ __forceinline__ uint32_t bf2_relu_sq(uint32_t a) {
    uint32_t r;
    asm("{\n.reg .b32 m;\nmax.bf16x2 m, %1, %2;\nmul.rn.bf16x2 %0, m, m;\n}" : "=r"(r) : "r"(a), "r"(0));
    return r;
}

__device__ __forceinline__ uint32_t pack_bf(float lo, float hi) {
    uint32_t r;
    asm("cvt.rn.bf16x2.f32 %0, %1, %2;" : "=r"(r) : "f"(hi), "f"(lo));
    return r;
}
__device__ __forceinline__ float bf_round(float v) { return __uint_as_float(pack_bf(0.f, v)); }
__device__ __forceinline__ float bf_lo(uint32_t w) { return __uint_as_float(w << 16); }
__device__ __forceinline__ float bf_hi(uint32_t w) { return __uint_as_float(w & 0xffff0000u); }

__device__ __forceinline__ float inv_std(float var) {
    float sd, inv;
    asm("sqrt.approx.ftz.f32 %0, %1;" : "=f"(sd) : "f"(bf_round(var + 1e-5f)));
    asm("rcp.approx.ftz.f32 %0, %1;" : "=f"(inv) : "f"(bf_round(sd)));
    return inv;
}

__device__ __forceinline__ void layernorm_row(const uint32_t (&w)[7], uint32_t dst, int lane) {
    const float shift = bf_lo(__shfl_sync(0xffffffffu, w[0], 0));
    float s = 0.f, ss = 0.f;
#pragma unroll
    for (int i = 0; i < 7; i++) {
        const float a = bf_lo(w[i]) - shift, b = bf_hi(w[i]) - shift;
        s += a + b;
        ss = fmaf(a, a, fmaf(b, b, ss));
    }
#pragma unroll
    for (int o = 16; o; o >>= 1) {
        s += __shfl_xor_sync(0xffffffffu, s, o);
        ss += __shfl_xor_sync(0xffffffffu, ss, o);
    }
    const float md = s * (1.f / DM);
    const float mean = bf_round(shift + md);
    const float inv = inv_std(bf_round(fmaxf(ss * (1.f / DM) - md * md, 0.f)));
#pragma unroll
    for (int i = 0; i < 7; i++) {
        const float a = bf_round(bf_lo(w[i]) - mean) * inv, b = bf_round(bf_hi(w[i]) - mean) * inv;
        sts32(dst + (i * 32 + lane) * 4, pack_bf(a, b));
    }
}

__device__ __forceinline__ void frags_w448(uint32_t (&a)[8][4], uint32_t src, int ew, int lane) {
    const int r = lane & 7, mi = lane >> 3;
    const uint32_t base = src + ((ew < 7 ? ew : 0) * 64 + (mi >> 1) * 8 + r) * 64;
#pragma unroll
    for (int ks = 0; ks < 4; ks++)
#pragma unroll
        for (int mt = 0; mt < 2; mt++)
            ldsm4t(a[ks * 2 + mt], base + ks * 1024 + (((2 * mt + (mi & 1)) ^ (r >> 1)) << 4));
}
__device__ __forceinline__ float2 gemv448(const uint32_t (&a)[8][4], uint32_t sb, int ew, int lane, int et) {
    const int g = lane >> 2, t = lane & 3;
    bar_sync(2, 256);
    if (ew < 7) {
        float c[4][4] = {};
        const uint32_t xb = sb + SM_XN + (g * 228 + ew * 32 + t) * 4;
#pragma unroll
        for (int ks = 0; ks < 4; ks++) {
            const uint32_t b0 = lds32(xb + ks * 32), b1 = lds32(xb + ks * 32 + 16);
            mma(c[(ks & 1) * 2], a[ks * 2], b0, b1);
            mma(c[(ks & 1) * 2 + 1], a[ks * 2 + 1], b0, b1);
        }
        const uint32_t rb = sb + SM_RED + (ew * 288 + t * 72 + g) * 4;
#pragma unroll
        for (int mt = 0; mt < 2; mt++) {
            sts32f(rb + mt * 64, c[mt][0] + c[2 + mt][0]);
            sts32f(rb + mt * 64 + 144, c[mt][1] + c[2 + mt][1]);
            sts32f(rb + mt * 64 + 32, c[mt][2] + c[2 + mt][2]);
            sts32f(rb + mt * 64 + 176, c[mt][3] + c[2 + mt][3]);
        }
    }
    bar_sync(2, 256);
    float2 acc = make_float2(0.f, 0.f);
    if (et < 128) {
        const uint32_t rb = sb + SM_RED + ((et >> 4) * 36 + (et & 15) * 2) * 4;
#pragma unroll
        for (int w = 0; w < 7; w++) {
            const float2 v = lds64f(rb + w * 1152);
            acc.x += v.x;
            acc.y += v.y;
        }
    }
    return acc;
}

struct Params {
    const __nv_bfloat16 *x, *k, *v, *wq, *wo, *w1, *b1, *w2, *b2;
    __nv_bfloat16* out;
    Exchange* xch;
    alignas(64) CUtensorMap map_wo, map_w1, map_w2;
};

__global__ void __launch_bounds__(NTHREADS, 1) fused_decode_kernel(const __grid_constant__ Params p) {
    extern __shared__ __align__(1024) unsigned char smem[];
    const uint32_t sb = (uint32_t)__cvta_generic_to_shared(smem);
    const int tid = threadIdx.x, warp = tid >> 5, lane = tid & 31;
    const int c = blockIdx.x;
    const char* kbase = (const char*)p.k + (size_t)c * (SK * DH * 2);
    const char* vbase = (const char*)p.v + (size_t)c * (SK * DH * 2);

    const int rot = (c * ROT) & (NCH - 1);
    Exchange* const gx = p.xch;

    if (tid == 128) l2_prefetch(p.wq + c * 14336, 28672, 1);
    if (warp == 4) {
        if (lane == 0) {
#pragma unroll
            for (int s = 0; s < NS; s++) {
                mbar_init(sb + BAR_FULL + 8 * s, 1);
                mbar_init(sb + BAR_EMPTY + 8 * s, 4);
            }
#pragma unroll
            for (int w = 0; w < 8; w++) {
                mbar_init(sb + BAR_WO + 8 * w, 1);
                mbar_init(sb + BAR_W1 + 8 * w, 1);
            }
            mbar_init(sb + BAR_DRY, 4);
            mbar_init(sb + BAR_WQ, 128);
            mbar_init(sb + BAR_Q, 1);
            mbar_init(sb + BAR_E1, 1);
            mbar_init(sb + BAR_X, 1);
            mbar_init(sb + BAR_X + 8, 1);
            ctl_store(sb + SM_PROG, 0);
            ctl_store(sb + SM_DEPTH, 2);
            asm volatile("fence.mbarrier_init.release.cluster;" ::: "memory");
        }
        __syncthreads();
        if (lane == 0) {
            uint64_t pol;
            asm volatile("createpolicy.fractional.L2::evict_first.b64 %0, 1.0;" : "=l"(pol));
            mbar_expect_tx(sb + BAR_FULL, CHUNK);
            bulk_load(sb + SM_RING, kbase + rot * CHUNK, CHUNK, sb + BAR_FULL, pol);
            spin_or(K1_DELAY, sb + BAR_WQ);
            int s = 1, sl = 0, landed = 0;
            uint32_t ph = 1, phl = 0;
#pragma unroll 1
            for (int i = 1; i <= 2 * NCH; i++) {
                const char* src = (i < NCH ? kbase : vbase) + ((i + rot) & (NCH - 1)) * CHUNK;
                for (int it = 0; landed < (i < 2 * NCH ? i + 1 - (int)ctl_load(sb + SM_DEPTH) : i); it++) {
                    if (mbar_test(sb + BAR_FULL + 8 * sl, phl) || it >= 16 * SPIN_LIMIT) {
                        asm volatile("red.relaxed.gpu.global.add.u32 [%0], 1;" ::"l"(gx->count + 32) : "memory");
                        ctl_store(sb + SM_PROG, ++landed);
                        if (++sl == NS) { sl = 0; phl ^= 1; }
                    } else {
                        __nanosleep(20);
                    }
                }
                if (i == 2 * NCH) break;
                mbar_wait(sb + BAR_EMPTY + 8 * s, ph);
                mbar_expect_tx(sb + BAR_FULL + 8 * s, CHUNK);
                bulk_load(sb + SM_RING + s * CHUNK, src, CHUNK, sb + BAR_FULL + 8 * s, pol);
                if (++s == NS) { s = 0; ph ^= 1; }
            }
        }
    } else if (warp < 4) {
        const int g = lane >> 2, t = lane & 3, r = lane & 7, mi = lane >> 3;
        {
            uint32_t* slot = gx->q + c * 128 + tid;
            uint32_t w = 0;
            xld32(w, slot, 0);
            const int row = tid >> 2, ch = tid & 3;
            const uint32_t dst = sb + SM_WQ + row * 64 + ((ch ^ ((row >> 1) & 3)) << 4);
            const __nv_bfloat16* src = p.wq + row * (NH * DH) + c * 32 + ch * 8;
#pragma unroll
            for (int i = 0; i < 14; i++)
                asm volatile("cp.async.cg.shared.global [%0], [%1], 16;" ::"r"(dst + i * 2048), "l"(src + i * 32 * (NH * DH)) : "memory");
            __syncthreads();
            asm volatile("cp.async.mbarrier.arrive.noinc.shared::cta.b64 [%0];" ::"r"(sb + BAR_WQ) : "memory");
            bar_sync(3, 256);
            w = poll32(slot, w, 0);
            xst32(slot, 0);
            sts32(sb + SM_Q + tid * 4, ~w);
        }
        bar_sync(1, 128);
        asm volatile("fence.proxy.async.shared::cta;" ::: "memory");
        if (tid == 0) mbar_arrive(sb + BAR_Q);
        int s = 0;
        uint32_t ph = 0;
        float rmax = -INFINITY;
        {
            uint32_t qf[32];
#pragma unroll
            for (int i = 0; i < 32; i++) qf[i] = lds32(sb + SM_Q + ((i ^ g) * 4 + t) * 4);
            uint32_t off[4];
#pragma unroll
            for (int i = 0; i < 4; i++)
                off[i] = sb + SM_RING + (warp * 16 + (mi & 1) * 8 + r) * 512 + (((2 * i + (mi >> 1)) ^ r) << 4);
            const bool owner = t == (g >> 1);
            uint32_t pdst = sb + SM_P + (t * 16 + warp * 4 + (g & 1)) * 2;
#pragma unroll 1
            for (int i = 0; i < NCH; i++) {
                mbar_wait(sb + BAR_FULL + 8 * s, ph);
                float acc[4][4] = {};
#pragma unroll
                for (int ks = 0; ks < 16; ks++) {
                    uint32_t a[4];
                    ldsm4(a, off[ks & 3] + s * CHUNK + (ks >> 2) * 128);
                    mma(acc[ks & 3], a, qf[2 * ks], qf[2 * ks + 1]);
                }
                __syncwarp();
                if (lane == 0) mbar_arrive(sb + BAR_EMPTY + 8 * s);
                float v[4];
#pragma unroll
                for (int e = 0; e < 4; e++) v[e] = (acc[0][e] + acc[1][e]) + (acc[2][e] + acc[3][e]);
                const float lo = (g & 1) ? v[1] : v[0], hi = (g & 1) ? v[3] : v[2];
                const uint32_t sc = pack_bf(bf_round(lo) * 0.0625f, bf_round(hi) * 0.0625f);
                if (owner) {
                    sts16(pdst, sc & 0xffffu);
                    sts16(pdst + 4, sc >> 16);
                    rmax = fmaxf(rmax, fmaxf(bf_lo(sc), bf_hi(sc)));
                }
                pdst += 128;
                if (++s == NS) { s = 0; ph ^= 1; }
            }
        }
        {
#pragma unroll
            for (int o = 16; o; o >>= 1) rmax = fmaxf(rmax, __shfl_xor_sync(0xffffffffu, rmax, o));
            if (lane == 0) sts32f(sb + SM_STAT + warp * 4, rmax);
            bar_sync(1, 128);
            const uint4 mx = lds128(sb + SM_STAT);
            const float m = fmaxf(fmaxf(__uint_as_float(mx.x), __uint_as_float(mx.y)),
                                  fmaxf(__uint_as_float(mx.z), __uint_as_float(mx.w)));
            float e[32];
            float sum = 0.f;
#pragma unroll
            for (int i = 0; i < 4; i++) {
                const uint4 w = lds128(sb + SM_P + (i * 128 + tid) * 16);
                const uint32_t ww[4] = {w.x, w.y, w.z, w.w};
#pragma unroll
                for (int j = 0; j < 4; j++) {
                    e[i * 8 + 2 * j] = __expf(bf_lo(ww[j]) - m);
                    e[i * 8 + 2 * j + 1] = __expf(bf_hi(ww[j]) - m);
                    sum += e[i * 8 + 2 * j] + e[i * 8 + 2 * j + 1];
                }
            }
#pragma unroll
            for (int o = 16; o; o >>= 1) sum += __shfl_xor_sync(0xffffffffu, sum, o);
            if (lane == 0) sts32f(sb + SM_STAT + 16 + warp * 4, sum);
            bar_sync(1, 128);
            const uint4 sm = lds128(sb + SM_STAT + 16);
            const float inv = 1.f / ((__uint_as_float(sm.x) + __uint_as_float(sm.y)) +
                                     (__uint_as_float(sm.z) + __uint_as_float(sm.w)));
#pragma unroll
            for (int i = 0; i < 4; i++) {
                uint4 w;
                w.x = pack_bf(e[i * 8 + 0] * inv, e[i * 8 + 1] * inv);
                w.y = pack_bf(e[i * 8 + 2] * inv, e[i * 8 + 3] * inv);
                w.z = pack_bf(e[i * 8 + 4] * inv, e[i * 8 + 5] * inv);
                w.w = pack_bf(e[i * 8 + 6] * inv, e[i * 8 + 7] * inv);
                sts128(sb + SM_P + (i * 128 + tid) * 16, w);
            }
            bar_sync(1, 128);
        }
        {
            uint32_t off[4];
#pragma unroll
            for (int i = 0; i < 4; i++)
                off[i] = sb + SM_RING + ((mi >> 1) * 8 + r) * 512 + warp * 128 + (((2 * i + (mi & 1)) ^ r) << 4);
            const uint32_t pmask = t == (g >> 1) ? ((g & 1) ? 0xffff0000u : 0x0000ffffu) : 0u;
            uint32_t* odst = gx->o + ((c & 15) * 8 + (c >> 4)) * 128 + (warp * 2 + (t >> 1)) * 16 + (g >> 1) * 4 +
                             (t & 1) * 2 + (g & 1);
            uint32_t lane2;
            asm volatile("mov.u32 %0, %%laneid;" : "=r"(lane2));
#pragma unroll 1
            for (int pass = 0; pass < 2; pass++) {
                int n = pass * NCH;
                asm volatile("" : "+r"(n));
                float acc[4][4] = {};
                uint32_t psrc = sb + SM_P + t * 32;
                uint32_t va[8][4], vb[8][4] = {};
                uint32_t pt[4] = {};
                uint32_t cur[4];
#pragma unroll
                for (int j = 0; j < 4; j++) cur[j] = off[j] + s * CHUNK;
                uint32_t bar = sb + BAR_FULL + 8 * s, ready = 0;
#pragma unroll 1
                for (int i = n; i > 0; i--) {
                    if (!ready) mbar_wait(bar, ph);
                    const bool wrap = bar == sb + BAR_FULL + 8 * (NS - 1);
                    const uint32_t barn = wrap ? sb + BAR_FULL : bar + 8;
                    ph ^= wrap;
                    const uint4 p0 = lds128(psrc), p1 = lds128(psrc + 16);
#pragma unroll
                    for (int j = 0; j < 2; j++) ldsm4t(va[j], cur[j & 3] + (j >> 2) * 8192);
                    uint32_t tok;
                    asm volatile("{\n.reg .pred p;\nmbarrier.test_wait.parity.shared::cta.b64 p, [%2], %3;\n"
                                 "selp.u32 %0, 1, 0, p;\nselp.u32 %1, %4, %5, p;\n}"
                                 : "=r"(ready), "=r"(tok) : "r"(barn), "r"(ph), "r"(lane), "r"(lane2) : "memory");
#pragma unroll
                    for (int j = 2; j < 8; j++) ldsm4t(va[j], cur[j & 3] + (j >> 2) * 8192);
#pragma unroll
                    for (int j = 0; j < 8; j++) mma(acc[j & 3], vb[j], pt[(j >> 2) * 2], pt[(j >> 2) * 2 + 1]);
#pragma unroll
                    for (int j = 0; j < 8; j++) ldsm4t(vb[j], cur[j & 3] + (2 + (j >> 2)) * 8192);
                    asm volatile("{\n.reg .pred p;\nsetp.eq.u32 p, %1, 0;\n@p mbarrier.arrive.shared::cta.b64 _, [%0];\n}"
                                 ::"r"(bar + 8 * NS), "r"(tok) : "memory");
                    mma(acc[0], va[0], p0.x & pmask, p0.y & pmask);
                    mma(acc[1], va[1], p0.x & pmask, p0.y & pmask);
                    mma(acc[2], va[2], p0.x & pmask, p0.y & pmask);
                    mma(acc[3], va[3], p0.x & pmask, p0.y & pmask);
                    mma(acc[0], va[4], p0.z & pmask, p0.w & pmask);
                    mma(acc[1], va[5], p0.z & pmask, p0.w & pmask);
                    mma(acc[2], va[6], p0.z & pmask, p0.w & pmask);
                    mma(acc[3], va[7], p0.z & pmask, p0.w & pmask);
                    pt[0] = p1.x & pmask;
                    pt[1] = p1.y & pmask;
                    pt[2] = p1.z & pmask;
                    pt[3] = p1.w & pmask;
                    psrc += 128;
                    bar = barn;
                    const uint32_t step = wrap ? -(NS - 1) * CHUNK : CHUNK;
#pragma unroll
                    for (int j = 0; j < 4; j++) cur[j] += step;
                }
#pragma unroll
                for (int j = 0; j < 8; j++) mma(acc[j & 3], vb[j], pt[(j >> 2) * 2], pt[(j >> 2) * 2 + 1]);
                float ev[4], od[4];
#pragma unroll
                for (int T = 0; T < 4; T++) {
                    ev[T] = acc[T][0] + acc[T][3];
                    od[T] = acc[T][1] + acc[T][2];
                }
                ev[0] += __shfl_xor_sync(0xffffffffu, ev[1], 1);
                od[0] += __shfl_xor_sync(0xffffffffu, od[1], 1);
                ev[2] += __shfl_xor_sync(0xffffffffu, ev[3], 1);
                od[2] += __shfl_xor_sync(0xffffffffu, od[3], 1);
                ev[0] += __shfl_xor_sync(0xffffffffu, ev[2], 2);
                od[0] += __shfl_xor_sync(0xffffffffu, od[2], 2);
                const float other = __shfl_xor_sync(0xffffffffu, (g & 1) ? ev[0] : od[0], 4);
                const uint32_t w = (g & 1) ? pack_bf(other, od[0]) : pack_bf(ev[0], other);
                xst32(odst, n ? w : EMPTY);
                __syncwarp();
                if (!n && lane == 0) mbar_arrive(sb + BAR_DRY);
                if (c < 112) {
                    bar_sync(1, 128);
                    if (tid == 0) {
                        const bool f1 = c < 56;
                        const uint32_t on = n ? 0xffffffffu : 0u;
                        mbar_wait(sb + BAR_W0, ~on & 1);
                        l2_prefetch(p.w1 + c * 7168, 14336, on);
                        spin((f1 ? W1_DELAY : PF_DELAY) & on);
                        if (!f1) {
                            l2_prefetch(p.w2 + (c - 56) * 14336, 28672, on);
                            mbar_wait(sb + BAR_E1, ~on & 1);
                            spin(W2_DELAY & on);
                        }
                        tile_loads(sb + (n ? SM_WX : SM_WO + 8192), f1 ? &p.map_w1 : &p.map_w2, f1 ? c * 32 : ((c - 56) % 28) * 16,
                                   n ? 0 : 1 << 20, f1 ? 64 : 224, f1 ? 4096 : 7168, sb + (n ? BAR_W1 : BAR_X), n ? 8 - f1 : 1);
                    }
                }
            }
        }
    } else {
        const int ew = warp - 5, et = tid - 160;
        const int r = lane & 7, mi = lane >> 3;
        {
            uint32_t w[7];
#pragma unroll
            for (int i = 0; i < 7; i++)
                asm volatile("ld.global.nc.u32 %0, [%1];" : "=r"(w[i]) : "l"((const uint32_t*)p.x + ew * 224 + i * 32 + lane));
            __syncthreads();
            layernorm_row(w, sb + SM_XN + ew * 912, lane);
            mbar_wait(sb + BAR_WQ, 0);
            uint32_t a[8][4];
            frags_w448(a, sb + SM_WQ, ew, lane);
            const float2 q = gemv448(a, sb, ew, lane, et);
            if (et < 128) {
                xst32(gx->q + ((et >> 4) * 16 + (c >> 3)) * 128 + (c & 7) * 16 + (et & 15), ~pack_bf(q.x, q.y));
                asm volatile("bar.arrive 3, 256;" ::: "memory");
            }
        }
        const int hh = c / 7, jj = c - hh * 7;
        const bool is_f1 = c < 56;
        const int cg = (c - 56) % 28, half = (c - 56) / 28;
        const int ht0 = (c - 112) * 7 + min(ew, 6);
        uint32_t side;
        asm volatile("ld.global.nc.u32 %0, [%1];" : "=r"(side)
                     : "l"(is_f1 ? p.b1 + c * 32 + (et & 15) * 2
                           : c < 112 ? p.b2 + cg * 16 + r * 2
                           : p.x + ((ht0 & 6) + (mi & 1)) * DM + (ht0 >> 3) * 32 + (r & 3) * 8 + (ht0 & 1) * 4 + (r >> 2) * 2));
        uint32_t seen_prog = 0;
#pragma unroll 1
        for (int pass = 0; pass < 2; pass++) {
            uint32_t live = pass;
            asm volatile("" : "+r"(live));
            const uint32_t want = 0u - live, wipe = ~want;
            const int et = pin(tid - 160), ew = et >> 5, lane = et & 31;
            const int g = lane >> 2, t = lane & 3, r = lane & 7, mi = lane >> 3;
            if (et == 0) {
                if (!live) mbar_wait(sb + BAR_Q, 0);
#pragma unroll 1
                for (int it = 0; it < SPIN_LIMIT; it++) {
                    const uint32_t prog = ctl_load(sb + SM_PROG);
                    int total = 0;
                    if (prog == seen_prog) __nanosleep(100);
                    if (prog != seen_prog || prog >= 2 * NCH - 8)
                        asm volatile("ld.relaxed.gpu.global.u32 %0, [%1];" : "=r"(total) : "l"(gx->count + 32) : "memory");
                    if (total >= ALL_CHUNKS - LIFT_LEFT) {
                        ctl_store(sb + SM_DEPTH, NS);
                    } else if (prog != seen_prog) {
                        const int lead = prog * NCTA - total;
                        ctl_store(sb + SM_DEPTH, lead >= LEAD1 ? 1 : lead >= LEAD2 ? 2 : lead >= LEAD2 - 128 ? 3 : lead >= LEAD2 - 256 ? 4 : NS);
                    }
                    seen_prog = prog;
                    if (live ? total >= ALL_CHUNKS - TRIG_LEFT : mbar_test(sb + BAR_DRY, 0)) break;
                }
                tile_loads(sb + SM_WO, &p.map_wo, jj * 64, live ? hh * 256 : 1 << 20, 32, 4096, sb + (live ? BAR_WO : BAR_X + 8),
                           c >= 112 ? 0 : live ? 8 : 1);
            } else if (et == 32 && live) {
                uint32_t seen;
                mbar_wait(sb + BAR_DRY, 0);
                asm volatile("atom.release.gpu.global.add.u32 %0, [%1], 1;" : "=r"(seen) : "l"(gx->count) : "memory");
                int it = 0;
                for (seen++; seen < NCTA && ++it < SPIN_LIMIT;) {
                    __nanosleep(512);
                    asm volatile("ld.relaxed.gpu.global.u32 %0, [%1];" : "=r"(seen) : "l"(gx->count) : "memory");
                }
                asm volatile("ld.acquire.gpu.global.u32 %0, [%1];" : "=r"(seen) : "l"(gx->count) : "memory");
            }
            __syncwarp();
            bar_sync(2, 256);
            if (c >= 112) {
                if (ew < 7) {
                    const bool odd = mi & 1;
                    const int ht = (c - 112) * 7 + ew;
                    float a0, a1;
                    uint32_t* const dst = gx->h + pin((((mi >> 1) * 14 + (ht >> 3)) * 8 + (ht & 6) + (mi & 1)) * 16 + (ht & 1) * 8 + r);
                    Poll<4, 128> in(gx->part + pin(ht * 512 + lane * 4), want, want);
                    in.finish([&] {
                        const uint4 (&v)[4] = in.v;
                        const float f0 = (__uint_as_float(v[0].x) + __uint_as_float(v[1].x)) + (__uint_as_float(v[2].x) + __uint_as_float(v[3].x));
                        const float f1 = (__uint_as_float(v[0].y) + __uint_as_float(v[1].y)) + (__uint_as_float(v[2].y) + __uint_as_float(v[3].y));
                        const float f2 = (__uint_as_float(v[0].z) + __uint_as_float(v[1].z)) + (__uint_as_float(v[2].z) + __uint_as_float(v[3].z));
                        const float f3 = (__uint_as_float(v[0].w) + __uint_as_float(v[1].w)) + (__uint_as_float(v[2].w) + __uint_as_float(v[3].w));
                        a0 = (odd ? f1 : f0) + __shfl_xor_sync(0xffffffffu, odd ? f0 : f1, 8);
                        a1 = (odd ? f3 : f2) + __shfl_xor_sync(0xffffffffu, odd ? f2 : f3, 8);
                    });
                    a0 += __shfl_xor_sync(0xffffffffu, a0, 16);
                    a1 += __shfl_xor_sync(0xffffffffu, a1, 16);
                    xst32(dst, bf2_add(side, pack_bf(a0, a1)) | wipe);
                }
                if (!live) bar_sync(5, 256);
                continue;
            }
            {
                uint32_t fa[4];
#pragma unroll
                for (int mt = 0; mt < 4; mt++)
                    fa[mt] = pin(sb + SM_WO + (ew * 32 + (mi >> 1) * 8 + r) * 128 + (((2 * mt + (mi & 1)) ^ r) << 4));
                const uint32_t wb = pin(sb + SM_RED + (ew * 544 + t * 136 + g * 2) * 4);
                const uint32_t rb = pin(sb + SM_RED + ((ew & 3) * 136 + ((ew >> 2) * 32 + (r >> 1) * 8 + mi * 2 + (r & 1)) * 2) * 4);
                uint32_t* const pdst = gx->part + pin((((jj * 8 + ew) * 2 + (lane >> 4)) * 16 + hh) * 32 + (lane & 15) * 2);
                Poll<1, 0> in(gx->o + pin((hh * 8 + g) * 128 + ew * 16 + t * 4), want, want);
                in.until(sb + BAR_WO + 8 * ew);
                uint32_t a[8][4];
#pragma unroll
                for (int mt = 0; mt < 4; mt++) ldsm4t(a[mt], fa[mt]);
#pragma unroll
                for (int mt = 0; mt < 4; mt++) ldsm4t(a[4 + mt], fa[mt] + 2048);
                float acc[4][4];
                in.finish([&] {
#pragma unroll
                    for (int mt = 0; mt < 4; mt++) mma0(acc[mt], a[mt], in.v[0].x, in.v[0].y);
#pragma unroll
                    for (int mt = 0; mt < 4; mt++) mma(acc[mt], a[4 + mt], in.v[0].z, in.v[0].w);
                });
#pragma unroll
                for (int mt = 0; mt < 4; mt++) {
                    sts64f(wb + mt * 128, acc[mt][0], acc[mt][1]);
                    sts64f(wb + mt * 128 + 64, acc[mt][2], acc[mt][3]);
                }
                bar_sync(2, 256);
                float2 v[8];
#pragma unroll
                for (int w = 0; w < 8; w++) v[w] = lds64f(rb + w * 2176);
                const float s0 = ((v[0].x + v[1].x) + (v[2].x + v[3].x)) + ((v[4].x + v[5].x) + (v[6].x + v[7].x));
                const float s1 = ((v[0].y + v[1].y) + (v[2].y + v[3].y)) + ((v[4].y + v[5].y) + (v[6].y + v[7].y));
                xst64(pdst, __float_as_uint(s0) | wipe, __float_as_uint(s1) | wipe);
            }
            if (et == 0 && live) mbar_arrive(sb + BAR_E1);
            const uint32_t wbar = sb + BAR_W1 + 8 * ew;
            if (is_f1) {
                constexpr uint32_t ONES = 0x3f803f80u;
                if (ew < 7) {
                    const int b = (et >> 4) & 7, pr = et & 15;
                    const uint32_t fa = pin(sb + SM_WX + (ew * 64 + (mi >> 1) * 8 + r) * 64 + (((mi & 1) ^ (r >> 1)) << 4));
                    const uint32_t wb = pin(sb + SM_RED + (ew * 288 + t * 72 + g) * 4);
                    const uint32_t sw = pin(sb + SM_RED + (ew * 288 + g * 36 + (t == (g >> 1) ? 32 : 34)) * 4);
                    const uint32_t rs = pin(sb + SM_RED + b * 144 + 128), rz = pin(sb + SM_RED + b * 144 + pr * 8);
                    const uint32_t cw = pin(sb + SM_XN + (ew * 32 + g + (t >> 1) * 16 + (t & 1) * 8) * 4), cr = pin(sb + SM_XN + pr * 8);
                    const bool odd = pin(g & 1);
                    uint32_t* const dst = gx->r + pin((((b >> 2) * 56 + c) * 4 + (b & 3)) * 16 + (pr & 3) * 4 + (pr >> 2));
                    Poll<2, 128> in(gx->h + pin(((c & 1) * 14 + ew * 2) * 128 + lane * 4), want, want);
                    mbar_wait(wbar, wipe & 1);
                    uint32_t a[8][4];
#pragma unroll
                    for (int ks = 0; ks < 4; ks++) {
                        ldsm4t(a[ks * 2], fa + ks * 1024);
                        ldsm4t(a[ks * 2 + 1], (fa ^ 32) + ks * 1024);
                    }
                    float cs[2][4] = {}, z[2][4], st[4];
#pragma unroll
                    for (int ks = 0; ks < 4; ks++) {
                        mma(cs[0], a[ks * 2], ONES, ONES);
                        mma(cs[1], a[ks * 2 + 1], ONES, ONES);
                    }
                    sts32f(cw, (t & 1) ? ((t & 2) ? cs[1][2] : cs[0][2]) : ((t & 2) ? cs[1][0] : cs[0][0]));
                    bar_sync(4, 224);
                    float2 cv[7];
#pragma unroll
                    for (int w = 0; w < 7; w++) cv[w] = lds64f(cr + w * 128);
                    const float cs0 = ((cv[0].x + cv[1].x) + (cv[2].x + cv[3].x)) + ((cv[4].x + cv[5].x) + cv[6].x);
                    const float cs1 = ((cv[0].y + cv[1].y) + (cv[2].y + cv[3].y)) + ((cv[4].y + cv[5].y) + cv[6].y);
                    const auto step = [&](int ks) {
                        const uint4& x = in.v[ks >> 1];
                        const uint32_t b0 = (ks & 1) ? x.z : x.x, b1 = (ks & 1) ? x.w : x.y;
                        const uint32_t sa[4] = {b0, ONES, b1, ONES};
                        if (ks == 0) {
                            mma0(st, sa, b0, b1);
                            mma0(z[0], a[0], b0, b1);
                            mma0(z[1], a[1], b0, b1);
                        } else {
                            mma(st, sa, b0, b1);
                            mma(z[0], a[ks * 2], b0, b1);
                            mma(z[1], a[ks * 2 + 1], b0, b1);
                        }
                    };
                    in.finish([&] {
                        step(0);
                        step(1);
                    });
                    step(2);
                    step(3);
                    sts64f(sw, odd ? st[3] : st[2], odd ? st[1] : st[0]);
#pragma unroll
                    for (int mt = 0; mt < 2; mt++) {
                        sts32f(wb + mt * 64, z[mt][0]);
                        sts32f(wb + mt * 64 + 144, z[mt][1]);
                        sts32f(wb + mt * 64 + 32, z[mt][2]);
                        sts32f(wb + mt * 64 + 176, z[mt][3]);
                    }
                    bar_sync(4, 224);
                    if (ew < 4) {
                        float2 sv[7], zv[7];
#pragma unroll
                        for (int w = 0; w < 7; w++) sv[w] = lds64f(rs + w * 1152);
#pragma unroll
                        for (int w = 0; w < 7; w++) zv[w] = lds64f(rz + w * 1152);
                        const float mu = (((sv[0].x + sv[1].x) + (sv[2].x + sv[3].x)) + ((sv[4].x + sv[5].x) + sv[6].x)) * (1.f / DM);
                        const float sq = ((sv[0].y + sv[1].y) + (sv[2].y + sv[3].y)) + ((sv[4].y + sv[5].y) + sv[6].y);
                        const float inv = inv_std(bf_round(fmaxf(fmaf(sq, 1.f / DM, -mu * mu), 0.f)));
                        const float mean = bf_round(mu);
                        const float z0 = ((zv[0].x + zv[1].x) + (zv[2].x + zv[3].x)) + ((zv[4].x + zv[5].x) + zv[6].x);
                        const float z1 = ((zv[0].y + zv[1].y) + (zv[2].y + zv[3].y)) + ((zv[4].y + zv[5].y) + zv[6].y);
                        const uint32_t u = pack_bf(fmaf(-mean, cs0, z0) * inv, fmaf(-mean, cs1, z1) * inv);
                        xst32(dst, bf2_relu_sq(bf2_add(u, side)) | wipe);
                    }
                }
            } else {
                const uint32_t fa = pin(sb + SM_WX + (ew * 224 + (mi >> 1) * 8 + r) * 32 + (((mi & 1) ^ (r >> 2)) << 4));
                const uint32_t wb = pin(sb + SM_XN + (ew * 160 + (t & 1) * 80 + (g >> 1) * 4 + (t >> 1) * 2 + (g & 1)) * 4);
                const uint32_t rb = pin(sb + SM_XN + (mi * 40 + r * 4) * 4);
                const bool upper = pin(t >> 1);
                uint32_t* const dst = (live ? (uint32_t*)p.out : gx->sink) + pin((half * 4 + mi) * 224 + cg * 8 + r);
                Poll<4, 128, true> in(gx->r + pin((half * 56 + ew * 7) * 64 + lane * 4), want, lane < 16 ? want : 0u,
                                      gx->h + pin((((c & 1) * 14 + (cg >> 1)) * 8 + half * 4 + mi) * 16 + (r & 3) * 4 +
                                                  (cg & 1) * 2 + (r >> 2)),
                                      ew == 0 ? want : 0u);
                mbar_wait(wbar, wipe & 1);
                uint32_t a[14][4];
#pragma unroll
                for (int ks = 0; ks < 14; ks++) ldsm4t(a[ks], fa + ks * 512);
                float acc[4][4];
                const auto step = [&](int i) {
                    mma(acc[0], a[4 * i], in.v[i].x, in.v[i].y);
                    mma(acc[1], a[4 * i + 1], in.v[i].z, in.v[i].w);
                    if (i < 3) {
                        mma(acc[2], a[4 * i + 2], in.v[i].x, in.v[i].y);
                        mma(acc[3], a[4 * i + 3], in.v[i].z, in.v[i].w);
                    }
                };
                in.finish([&] {
                    mma0(acc[0], a[0], in.v[0].x, in.v[0].y);
                    mma0(acc[1], a[1], in.v[0].z, in.v[0].w);
                    mma0(acc[2], a[2], in.v[0].x, in.v[0].y);
                    mma0(acc[3], a[3], in.v[0].z, in.v[0].w);
                    step(1);
                });
                step(2);
                step(3);
                sts32f(wb, upper ? acc[2][0] + acc[3][0] : acc[0][0] + acc[1][0]);
                sts32f(wb + 160, upper ? acc[2][1] + acc[3][1] : acc[0][1] + acc[1][1]);
                sts32f(wb + 64, upper ? acc[2][2] + acc[3][2] : acc[0][2] + acc[1][2]);
                sts32f(wb + 224, upper ? acc[2][3] + acc[3][3] : acc[0][3] + acc[1][3]);
                if (ew == 0) {
                    bar_sync(2, 256);
                    float x[8], y[8];
#pragma unroll
                    for (int w = 0; w < 8; w++) {
                        const uint4 q = lds128(rb + w * 640);
                        x[w] = __uint_as_float(q.x) + __uint_as_float(q.z);
                        y[w] = __uint_as_float(q.y) + __uint_as_float(q.w);
                    }
                    const float s0 = ((x[0] + x[1]) + (x[2] + x[3])) + ((x[4] + x[5]) + (x[6] + x[7]));
                    const float s1 = ((y[0] + y[1]) + (y[2] + y[3])) + ((y[4] + y[5]) + (y[6] + y[7]));
                    *dst = bf2_add(in.word, bf2_add(pack_bf(s0, s1), side));
                } else {
                    asm volatile("bar.arrive 2, 256;" ::: "memory");
                    if (c == 56 && et == 32 && live) {
                        xst32(gx->count, 0);
                        xst32(gx->count + 32, 0);
                    }
                }
            }
            if (!live) bar_sync(5, 256);
        }
    }
}

using EncodeFn = CUresult (*)(CUtensorMap*, CUtensorMapDataType, cuuint32_t, void*, const cuuint64_t*, const cuuint64_t*,
                              const cuuint32_t*, const cuuint32_t*, CUtensorMapInterleave, CUtensorMapSwizzle,
                              CUtensorMapL2promotion, CUtensorMapFloatOOBfill);

void encode_map(EncodeFn fn, CUtensorMap* map, const void* base, int rows, int cols, int box_rows, int box_cols,
                CUtensorMapSwizzle swizzle) {
    const cuuint64_t dims[2] = {(cuuint64_t)cols, (cuuint64_t)rows};
    const cuuint64_t strides[1] = {(cuuint64_t)cols * 2};
    const cuuint32_t box[2] = {(cuuint32_t)box_cols, (cuuint32_t)box_rows};
    const cuuint32_t steps[2] = {1, 1};
    fn(map, CU_TENSOR_MAP_DATA_TYPE_BFLOAT16, 2, const_cast<void*>(base), dims, strides, box, steps,
       CU_TENSOR_MAP_INTERLEAVE_NONE, swizzle, CU_TENSOR_MAP_L2_PROMOTION_L2_128B, CU_TENSOR_MAP_FLOAT_OOB_FILL_NONE);
}

}

extern "C" void kernel_launch(void* const* d_in, const int* in_sizes, int n_in, void* d_out, int out_size) {
    (void)in_sizes; (void)n_in; (void)out_size;
    Params p;
    p.x = (const __nv_bfloat16*)d_in[0];
    p.k = (const __nv_bfloat16*)d_in[1];
    p.v = (const __nv_bfloat16*)d_in[2];
    p.wq = (const __nv_bfloat16*)d_in[3];
    p.wo = (const __nv_bfloat16*)d_in[4];
    p.w1 = (const __nv_bfloat16*)d_in[6];
    p.b1 = (const __nv_bfloat16*)d_in[7];
    p.w2 = (const __nv_bfloat16*)d_in[8];
    p.b2 = (const __nv_bfloat16*)d_in[9];
    p.out = (__nv_bfloat16*)d_out;
    cudaGetSymbolAddress((void**)&p.xch, g_x);
    void* fn = nullptr;
    cudaDriverEntryPointQueryResult found;
    cudaGetDriverEntryPoint("cuTensorMapEncodeTiled", &fn, cudaEnableDefault, &found);
    encode_map((EncodeFn)fn, &p.map_wo, p.wo, NH * DH, DM, 32, 64, CU_TENSOR_MAP_SWIZZLE_128B);
    encode_map((EncodeFn)fn, &p.map_w1, p.w1, DM, FF, 64, 32, CU_TENSOR_MAP_SWIZZLE_64B);
    encode_map((EncodeFn)fn, &p.map_w2, p.w2, FF, DM, 224, 16, CU_TENSOR_MAP_SWIZZLE_32B);
    cudaFuncSetAttribute(fused_decode_kernel, cudaFuncAttributeMaxDynamicSharedMemorySize, SM_TOTAL);
    fused_decode_kernel<<<NCTA, NTHREADS, SM_TOTAL>>>(p);
}
```

```cpp
#include <cuda.h>
#include <cuda_runtime.h>
#include <cuda_bf16.h>
#include <stdint.h>

namespace {

constexpr int DM = 448, NH = 16, SK = 4096, DH = 256, FF = 1792;
constexpr int NCTA = 128;
constexpr int CHUNK = 32768;
constexpr int NCH = SK / 64;
constexpr int NS = 5;
constexpr int ALL_CHUNKS = NCTA * 2 * NCH;
constexpr int LEAD1 = 256;
constexpr int LEAD2 = -128;
constexpr int LIFT_LEFT = 350;
constexpr int TRIG_LEFT = 220;
constexpr int K1_DELAY = 2000;
constexpr int W1_DELAY = 600;
constexpr int PF_DELAY = 500;
constexpr int W2_DELAY = 600;
constexpr int ROT = 32;
constexpr int NTHREADS = 13 * 32;
constexpr int SPIN_LIMIT = 1 << 18;
constexpr int WAIT_LIMIT = 1 << 14;

constexpr int SM_RING = 0;
constexpr int SM_WX = 0;
constexpr int SM_WQ = NS * CHUNK;
constexpr int SM_WO = SM_WQ;
constexpr int SM_P = SM_WQ + 32768;
constexpr int SM_RED = SM_P + 8192;
constexpr int SM_XN = SM_RED + 8 * 544 * 4;
constexpr int SM_Q = SM_XN + 8 * 456 * 2;
constexpr int SM_STAT = SM_Q + 512;
constexpr int SM_PROG = SM_STAT + 32, SM_DEPTH = SM_STAT + 36;
constexpr int SM_BAR = SM_STAT + 64;
constexpr int BAR_FULL = SM_BAR, BAR_EMPTY = BAR_FULL + 8 * NS, BAR_WO = BAR_EMPTY + 8 * NS, BAR_DRY = BAR_WO + 64,
              BAR_WQ = BAR_DRY + 8, BAR_Q = BAR_WQ + 8, BAR_W0 = BAR_WO + 56, BAR_E1 = BAR_Q + 8, BAR_X = BAR_E1 + 8,
              BAR_W1 = BAR_X + 16;
constexpr int SM_TOTAL = BAR_W1 + 64;
static_assert(SM_TOTAL <= 232448, "shared memory budget");

struct Exchange {
    uint32_t q[NCTA * 128];
    uint32_t o[NH * 8 * 128];
    uint32_t part[14 * 8 * 16 * 32];
    uint32_t h[2 * 14 * 8 * 16];
    uint32_t r[2 * 56 * 4 * 16];
    uint32_t count[64];
    uint32_t sink[8 * 224];
};
__device__ __align__(128) Exchange g_x;

__device__ __forceinline__ void mbar_init(uint32_t bar, uint32_t count) {
    asm volatile("mbarrier.init.shared::cta.b64 [%0], %1;" ::"r"(bar), "r"(count) : "memory");
}
__device__ __forceinline__ void mbar_arrive(uint32_t bar) {
    asm volatile("mbarrier.arrive.shared::cta.b64 _, [%0];" ::"r"(bar) : "memory");
}
__device__ __forceinline__ void mbar_expect_tx(uint32_t bar, uint32_t bytes) {
    asm volatile("mbarrier.arrive.expect_tx.shared::cta.b64 _, [%0], %1;" ::"r"(bar), "r"(bytes) : "memory");
}
__device__ __forceinline__ void mbar_wait(uint32_t bar, uint32_t parity) {
    uint32_t done;
    int it = 0;
    do {
        asm volatile("{\n.reg .pred p;\nmbarrier.try_wait.parity.shared::cta.b64 p, [%1], %2;\nselp.u32 %0, 1, 0, p;\n}"
                     : "=r"(done) : "r"(bar), "r"(parity) : "memory");
    } while (!done && ++it < WAIT_LIMIT);
}
__device__ __forceinline__ uint32_t mbar_test(uint32_t bar, uint32_t parity) {
    uint32_t done;
    asm volatile("{\n.reg .pred p;\nmbarrier.test_wait.parity.shared::cta.b64 p, [%1], %2;\nselp.u32 %0, 1, 0, p;\n}"
                 : "=r"(done) : "r"(bar), "r"(parity) : "memory");
    return done;
}
__device__ __forceinline__ void spin(uint32_t cycles) {
    const uint32_t t0 = (uint32_t)clock();
    do {
    } while ((uint32_t)clock() - t0 < cycles);
}
__device__ __forceinline__ void spin_or(uint32_t cycles, uint32_t bar) {
    const uint32_t t0 = (uint32_t)clock();
    do {
    } while (!mbar_test(bar, 0) && (uint32_t)clock() - t0 < cycles);
}
__device__ __forceinline__ void l2_prefetch(const void* src, uint32_t bytes, uint32_t on) {
    asm volatile("{\n.reg .pred p;\nsetp.ne.u32 p, %2, 0;\n@p cp.async.bulk.prefetch.L2.global [%0], %1;\n}"
                 ::"l"(src), "r"(bytes), "r"(on) : "memory");
}
__device__ __forceinline__ void bulk_load(uint32_t dst, const void* src, uint32_t bytes, uint32_t bar, uint64_t pol) {
    asm volatile("cp.async.bulk.shared::cluster.global.mbarrier::complete_tx::bytes.L2::cache_hint [%0], [%1], %2, [%3], %4;"
                 ::"r"(dst), "l"(src), "r"(bytes), "r"(bar), "l"(pol) : "memory");
}
__device__ __forceinline__ void tile_loads(uint32_t dst, const CUtensorMap* map, int col, int row, int rows, uint32_t bytes,
                                           uint32_t bar, int n) {
#pragma unroll 1
    for (int i = 0; i < n; i++, dst += bytes, row += rows, bar += 8) {
        mbar_expect_tx(bar, bytes);
        asm volatile("cp.async.bulk.tensor.2d.shared::cluster.global.mbarrier::complete_tx::bytes [%0], [%1, {%2, %3}], [%4];"
                     ::"r"(dst), "l"(map), "r"(col), "r"(row), "r"(bar) : "memory");
    }
}
__device__ __forceinline__ void bar_sync(int id, int n) { asm volatile("bar.sync %0, %1;" ::"r"(id), "r"(n) : "memory"); }

__device__ __forceinline__ void ldsm4(uint32_t (&r)[4], uint32_t a) {
    asm volatile("ldmatrix.sync.aligned.m8n8.x4.shared.b16 {%0,%1,%2,%3}, [%4];"
                 : "=r"(r[0]), "=r"(r[1]), "=r"(r[2]), "=r"(r[3]) : "r"(a) : "memory");
}
__device__ __forceinline__ void ldsm4t(uint32_t (&r)[4], uint32_t a) {
    asm volatile("ldmatrix.sync.aligned.m8n8.x4.trans.shared.b16 {%0,%1,%2,%3}, [%4];"
                 : "=r"(r[0]), "=r"(r[1]), "=r"(r[2]), "=r"(r[3]) : "r"(a) : "memory");
}
__device__ __forceinline__ void mma(float (&c)[4], const uint32_t (&a)[4], uint32_t b0, uint32_t b1) {
    asm volatile("mma.sync.aligned.m16n8k16.row.col.f32.bf16.bf16.f32 {%0,%1,%2,%3}, {%4,%5,%6,%7}, {%8,%9}, {%0,%1,%2,%3};"
                 : "+f"(c[0]), "+f"(c[1]), "+f"(c[2]), "+f"(c[3])
                 : "r"(a[0]), "r"(a[1]), "r"(a[2]), "r"(a[3]), "r"(b0), "r"(b1));
}
__device__ __forceinline__ void mma0(float (&c)[4], const uint32_t (&a)[4], uint32_t b0, uint32_t b1) {
    asm volatile("mma.sync.aligned.m16n8k16.row.col.f32.bf16.bf16.f32 {%0,%1,%2,%3}, {%4,%5,%6,%7}, {%8,%9}, {%10,%10,%10,%10};"
                 : "=f"(c[0]), "=f"(c[1]), "=f"(c[2]), "=f"(c[3])
                 : "r"(a[0]), "r"(a[1]), "r"(a[2]), "r"(a[3]), "r"(b0), "r"(b1), "f"(0.f));
}
__device__ __forceinline__ uint32_t lds32(uint32_t a) {
    uint32_t v;
    asm volatile("ld.shared.u32 %0, [%1];" : "=r"(v) : "r"(a) : "memory");
    return v;
}
__device__ __forceinline__ uint32_t ctl_load(uint32_t a) {
    uint32_t v;
    asm volatile("ld.volatile.shared.u32 %0, [%1];" : "=r"(v) : "r"(a) : "memory");
    return v;
}
__device__ __forceinline__ void ctl_store(uint32_t a, uint32_t v) {
    asm volatile("st.volatile.shared.u32 [%0], %1;" ::"r"(a), "r"(v) : "memory");
}
__device__ __forceinline__ float2 lds64f(uint32_t a) {
    float2 v;
    asm volatile("ld.shared.v2.f32 {%0,%1}, [%2];" : "=f"(v.x), "=f"(v.y) : "r"(a) : "memory");
    return v;
}
__device__ __forceinline__ uint4 lds128(uint32_t a) {
    uint4 v;
    asm volatile("ld.shared.v4.u32 {%0,%1,%2,%3}, [%4];" : "=r"(v.x), "=r"(v.y), "=r"(v.z), "=r"(v.w) : "r"(a) : "memory");
    return v;
}
__device__ __forceinline__ void sts16(uint32_t a, uint32_t v) {
    asm volatile("st.shared.u16 [%0], %1;" ::"r"(a), "h"((unsigned short)v) : "memory");
}
__device__ __forceinline__ void sts32(uint32_t a, uint32_t v) {
    asm volatile("st.shared.u32 [%0], %1;" ::"r"(a), "r"(v) : "memory");
}
__device__ __forceinline__ void sts32f(uint32_t a, float v) {
    asm volatile("st.shared.f32 [%0], %1;" ::"r"(a), "f"(v) : "memory");
}
__device__ __forceinline__ void sts64f(uint32_t a, float x, float y) {
    asm volatile("st.shared.v2.f32 [%0], {%1,%2};" ::"r"(a), "f"(x), "f"(y) : "memory");
}
__device__ __forceinline__ void sts128(uint32_t a, uint4 v) {
    asm volatile("st.shared.v4.u32 [%0], {%1,%2,%3,%4};" ::"r"(a), "r"(v.x), "r"(v.y), "r"(v.z), "r"(v.w) : "memory");
}

constexpr uint32_t EMPTY = 0xffffffffu;
__device__ __forceinline__ void xld32(uint32_t& v, const uint32_t* p, uint32_t empty) {
    asm volatile("{\n.reg .pred p;\nsetp.eq.u32 p, %0, %2;\n@p ld.relaxed.gpu.global.u32 %0, [%1];\n}"
                 : "+r"(v) : "l"(p), "r"(empty) : "memory");
}
__device__ __forceinline__ void xld128(uint4& v, const uint32_t* p, uint32_t top) {
    asm volatile("{\n.reg .pred p;\nsetp.eq.u32 p, %5, 0xffffffff;\n@p ld.relaxed.gpu.global.v4.u32 {%0,%1,%2,%3}, [%4];\n}"
                 : "+r"(v.x), "+r"(v.y), "+r"(v.z), "+r"(v.w) : "l"(p), "r"(top) : "memory");
}
__device__ __forceinline__ void xst32(uint32_t* p, uint32_t v) {
    asm volatile("st.relaxed.gpu.global.u32 [%0], %1;" ::"l"(p), "r"(v) : "memory");
}
__device__ __forceinline__ void xst64(uint32_t* p, uint32_t a, uint32_t b) {
    asm volatile("st.relaxed.gpu.global.v2.u32 [%0], {%1,%2};" ::"l"(p), "r"(a), "r"(b) : "memory");
}
__device__ __forceinline__ uint32_t top_word(const uint4& v) { return max(__vimax3_u32(v.x, v.y, v.z), v.w); }
template <int N, int STRIDE, bool WORD = false>
struct Poll {
    uint4 v[N];
    uint32_t top[N], word, want;
    const uint32_t *src, *wsrc;
    int left;
    __device__ __forceinline__ Poll(const uint32_t* s, uint32_t init, uint32_t init_last, const uint32_t* ws = nullptr,
                                    uint32_t init_word = 0)
        : word(init_word), want(init), src(s), wsrc(ws), left(init ? SPIN_LIMIT : 2) {
#pragma unroll
        for (int i = 0; i < N; i++) {
            top[i] = i == N - 1 ? init_last : init;
            v[i] = make_uint4(top[i], top[i], top[i], top[i]);
        }
    }
    __device__ __forceinline__ void issue() {
#pragma unroll
        for (int i = 0; i < N; i++) xld128(v[i], src + i * STRIDE, top[i]);
        if (WORD) xld32(word, wsrc, EMPTY);
        left--;
    }
    __device__ __forceinline__ bool missing() {
        uint32_t m = WORD ? word : 0;
#pragma unroll
        for (int i = 0; i < N; i++) {
            top[i] = top_word(v[i]);
            m = max(m, top[i]);
        }
        return __any_sync(0xffffffffu, m == want && left > 0);
    }
    __device__ __forceinline__ void until(uint32_t bar) {
#pragma unroll 1
        while (!mbar_test(bar, 0)) {
            issue();
            if (!missing()) break;
        }
        mbar_wait(bar, ~want & 1);
    }
    template <class F>
    __device__ __forceinline__ void finish(F use) {
        bool again;
#pragma unroll 1
        do {
            issue();
            again = missing();
            use();
        } while (again);
    }
};
__device__ __forceinline__ uint32_t poll32(const uint32_t* src, uint32_t init, uint32_t empty) {
    int left = SPIN_LIMIT;
#pragma unroll 1
    do {
        xld32(init, src, empty);
        left--;
    } while (__any_sync(0xffffffffu, init == empty && left > 0));
    return init;
}
__device__ __forceinline__ uint32_t pin(uint32_t v) {
    asm volatile("shfl.sync.bfly.b32 %0, %0, 0, 0x1f, 0xffffffff;" : "+r"(v));
    return v;
}
__device__ __forceinline__ uint32_t bf2_add(uint32_t a, uint32_t b) {
    uint32_t r;
    asm("add.rn.bf16x2 %0, %1, %2;" : "=r"(r) : "r"(a), "r"(b));
    return r;
}
__device__ __forceinline__ uint32_t bf2_relu_sq(uint32_t a) {
    uint32_t r;
    asm("{\n.reg .b32 m;\nmax.bf16x2 m, %1, %2;\nmul.rn.bf16x2 %0, m, m;\n}" : "=r"(r) : "r"(a), "r"(0));
    return r;
}

__device__ __forceinline__ uint32_t pack_bf(float lo, float hi) {
    uint32_t r;
    asm("cvt.rn.bf16x2.f32 %0, %1, %2;" : "=r"(r) : "f"(hi), "f"(lo));
    return r;
}
__device__ __forceinline__ float bf_round(float v) { return __uint_as_float(pack_bf(0.f, v)); }
__device__ __forceinline__ float bf_lo(uint32_t w) { return __uint_as_float(w << 16); }
__device__ __forceinline__ float bf_hi(uint32_t w) { return __uint_as_float(w & 0xffff0000u); }

__device__ __forceinline__ float inv_std(float var) {
    float sd, inv;
    asm("sqrt.approx.ftz.f32 %0, %1;" : "=f"(sd) : "f"(bf_round(var + 1e-5f)));
    asm("rcp.approx.ftz.f32 %0, %1;" : "=f"(inv) : "f"(bf_round(sd)));
    return inv;
}

__device__ __forceinline__ void layernorm_row(const uint32_t (&w)[7], uint32_t dst, int lane) {
    const float shift = bf_lo(__shfl_sync(0xffffffffu, w[0], 0));
    float s = 0.f, ss = 0.f;
#pragma unroll
    for (int i = 0; i < 7; i++) {
        const float a = bf_lo(w[i]) - shift, b = bf_hi(w[i]) - shift;
        s += a + b;
        ss = fmaf(a, a, fmaf(b, b, ss));
    }
#pragma unroll
    for (int o = 16; o; o >>= 1) {
        s += __shfl_xor_sync(0xffffffffu, s, o);
        ss += __shfl_xor_sync(0xffffffffu, ss, o);
    }
    const float md = s * (1.f / DM);
    const float mean = bf_round(shift + md);
    const float inv = inv_std(bf_round(fmaxf(ss * (1.f / DM) - md * md, 0.f)));
#pragma unroll
    for (int i = 0; i < 7; i++) {
        const float a = bf_round(bf_lo(w[i]) - mean) * inv, b = bf_round(bf_hi(w[i]) - mean) * inv;
        sts32(dst + (i * 32 + lane) * 4, pack_bf(a, b));
    }
}

__device__ __forceinline__ void frags_w448(uint32_t (&a)[8][4], uint32_t src, int ew, int lane) {
    const int r = lane & 7, mi = lane >> 3;
    const uint32_t base = src + ((ew < 7 ? ew : 0) * 64 + (mi >> 1) * 8 + r) * 64;
#pragma unroll
    for (int ks = 0; ks < 4; ks++)
#pragma unroll
        for (int mt = 0; mt < 2; mt++)
            ldsm4t(a[ks * 2 + mt], base + ks * 1024 + (((2 * mt + (mi & 1)) ^ (r >> 1)) << 4));
}
__device__ __forceinline__ float2 gemv448(const uint32_t (&a)[8][4], uint32_t sb, int ew, int lane, int et) {
    const int g = lane >> 2, t = lane & 3;
    bar_sync(2, 256);
    if (ew < 7) {
        float c[4][4] = {};
        const uint32_t xb = sb + SM_XN + (g * 228 + ew * 32 + t) * 4;
#pragma unroll
        for (int ks = 0; ks < 4; ks++) {
            const uint32_t b0 = lds32(xb + ks * 32), b1 = lds32(xb + ks * 32 + 16);
            mma(c[(ks & 1) * 2], a[ks * 2], b0, b1);
            mma(c[(ks & 1) * 2 + 1], a[ks * 2 + 1], b0, b1);
        }
        const uint32_t rb = sb + SM_RED + (ew * 288 + t * 72 + g) * 4;
#pragma unroll
        for (int mt = 0; mt < 2; mt++) {
            sts32f(rb + mt * 64, c[mt][0] + c[2 + mt][0]);
            sts32f(rb + mt * 64 + 144, c[mt][1] + c[2 + mt][1]);
            sts32f(rb + mt * 64 + 32, c[mt][2] + c[2 + mt][2]);
            sts32f(rb + mt * 64 + 176, c[mt][3] + c[2 + mt][3]);
        }
    }
    bar_sync(2, 256);
    float2 acc = make_float2(0.f, 0.f);
    if (et < 128) {
        const uint32_t rb = sb + SM_RED + ((et >> 4) * 36 + (et & 15) * 2) * 4;
#pragma unroll
        for (int w = 0; w < 7; w++) {
            const float2 v = lds64f(rb + w * 1152);
            acc.x += v.x;
            acc.y += v.y;
        }
    }
    return acc;
}

struct Params {
    const __nv_bfloat16 *x, *k, *v, *wq, *wo, *w1, *b1, *w2, *b2;
    __nv_bfloat16* out;
    Exchange* xch;
    alignas(64) CUtensorMap map_wo, map_w1, map_w2;
};

__global__ void __launch_bounds__(NTHREADS, 1) fused_decode_kernel(const __grid_constant__ Params p) {
    extern __shared__ __align__(1024) unsigned char smem[];
    const uint32_t sb = (uint32_t)__cvta_generic_to_shared(smem);
    const int tid = threadIdx.x, warp = tid >> 5, lane = tid & 31;
    const int c = blockIdx.x;
    const char* kbase = (const char*)p.k + (size_t)c * (SK * DH * 2);
    const char* vbase = (const char*)p.v + (size_t)c * (SK * DH * 2);

    const int rot = (c * ROT) & (NCH - 1);
    Exchange* const gx = p.xch;

    if (tid == 128) l2_prefetch(p.wq + c * 14336, 28672, 1);
    if (warp == 4) {
        if (lane == 0) {
#pragma unroll
            for (int s = 0; s < NS; s++) {
                mbar_init(sb + BAR_FULL + 8 * s, 1);
                mbar_init(sb + BAR_EMPTY + 8 * s, 4);
            }
#pragma unroll
            for (int w = 0; w < 8; w++) {
                mbar_init(sb + BAR_WO + 8 * w, 1);
                mbar_init(sb + BAR_W1 + 8 * w, 1);
            }
            mbar_init(sb + BAR_DRY, 4);
            mbar_init(sb + BAR_WQ, 128);
            mbar_init(sb + BAR_Q, 1);
            mbar_init(sb + BAR_E1, 1);
            mbar_init(sb + BAR_X, 1);
            mbar_init(sb + BAR_X + 8, 1);
            ctl_store(sb + SM_PROG, 0);
            ctl_store(sb + SM_DEPTH, 2);
            asm volatile("fence.mbarrier_init.release.cluster;" ::: "memory");
        }
        __syncthreads();
        if (lane == 0) {
            uint64_t pol;
            asm volatile("createpolicy.fractional.L2::evict_first.b64 %0, 1.0;" : "=l"(pol));
            mbar_expect_tx(sb + BAR_FULL, CHUNK);
            bulk_load(sb + SM_RING, kbase + rot * CHUNK, CHUNK, sb + BAR_FULL, pol);
            spin_or(K1_DELAY, sb + BAR_WQ);
            int s = 1, sl = 0, landed = 0;
            uint32_t ph = 1, phl = 0;
#pragma unroll 1
            for (int i = 1; i <= 2 * NCH; i++) {
                const char* src = (i < NCH ? kbase : vbase) + ((i + rot) & (NCH - 1)) * CHUNK;
                for (int it = 0; landed < (i < 2 * NCH ? i + 1 - (int)ctl_load(sb + SM_DEPTH) : i); it++) {
                    if (mbar_test(sb + BAR_FULL + 8 * sl, phl) || it >= 4 * SPIN_LIMIT) {
                        asm volatile("red.relaxed.gpu.global.add.u32 [%0], 1;" ::"l"(gx->count + 32) : "memory");
                        ctl_store(sb + SM_PROG, ++landed);
                        if (++sl == NS) { sl = 0; phl ^= 1; }
                    } else {
                        __nanosleep(20);
                    }
                }
                if (i == 2 * NCH) break;
                mbar_wait(sb + BAR_EMPTY + 8 * s, ph);
                mbar_expect_tx(sb + BAR_FULL + 8 * s, CHUNK);
                bulk_load(sb + SM_RING + s * CHUNK, src, CHUNK, sb + BAR_FULL + 8 * s, pol);
                if (++s == NS) { s = 0; ph ^= 1; }
            }
        }
    } else if (warp < 4) {
        const int g = lane >> 2, t = lane & 3, r = lane & 7, mi = lane >> 3;
        {
            uint32_t* slot = gx->q + c * 128 + tid;
            uint32_t w = 0;
            xld32(w, slot, 0);
            const int row = tid >> 2, ch = tid & 3;
            const uint32_t dst = sb + SM_WQ + row * 64 + ((ch ^ ((row >> 1) & 3)) << 4);
            const __nv_bfloat16* src = p.wq + row * (NH * DH) + c * 32 + ch * 8;
#pragma unroll
            for (int i = 0; i < 14; i++)
                asm volatile("cp.async.cg.shared.global [%0], [%1], 16;" ::"r"(dst + i * 2048), "l"(src + i * 32 * (NH * DH)) : "memory");
            __syncthreads();
            asm volatile("cp.async.mbarrier.arrive.noinc.shared::cta.b64 [%0];" ::"r"(sb + BAR_WQ) : "memory");
            bar_sync(3, 256);
            w = poll32(slot, w, 0);
            xst32(slot, 0);
            sts32(sb + SM_Q + tid * 4, ~w);
        }
        bar_sync(1, 128);
        asm volatile("fence.proxy.async.shared::cta;" ::: "memory");
        if (tid == 0) mbar_arrive(sb + BAR_Q);
        int s = 0;
        uint32_t ph = 0;
        float rmax = -INFINITY;
        {
            uint32_t qf[32];
#pragma unroll
            for (int i = 0; i < 32; i++) qf[i] = lds32(sb + SM_Q + ((i ^ g) * 4 + t) * 4);
            uint32_t off[4];
#pragma unroll
            for (int i = 0; i < 4; i++)
                off[i] = sb + SM_RING + (warp * 16 + (mi & 1) * 8 + r) * 512 + (((2 * i + (mi >> 1)) ^ r) << 4);
            const bool owner = t == (g >> 1);
            uint32_t pdst = sb + SM_P + (t * 16 + warp * 4 + (g & 1)) * 2;
#pragma unroll 1
            for (int i = 0; i < NCH; i++) {
                mbar_wait(sb + BAR_FULL + 8 * s, ph);
                float acc[4][4] = {};
#pragma unroll
                for (int ks = 0; ks < 16; ks++) {
                    uint32_t a[4];
                    ldsm4(a, off[ks & 3] + s * CHUNK + (ks >> 2) * 128);
                    mma(acc[ks & 3], a, qf[2 * ks], qf[2 * ks + 1]);
                }
                __syncwarp();
                if (lane == 0) mbar_arrive(sb + BAR_EMPTY + 8 * s);
                float v[4];
#pragma unroll
                for (int e = 0; e < 4; e++) v[e] = (acc[0][e] + acc[1][e]) + (acc[2][e] + acc[3][e]);
                const float lo = (g & 1) ? v[1] : v[0], hi = (g & 1) ? v[3] : v[2];
                const uint32_t sc = pack_bf(bf_round(lo) * 0.0625f, bf_round(hi) * 0.0625f);
                if (owner) {
                    sts16(pdst, sc & 0xffffu);
                    sts16(pdst + 4, sc >> 16);
                    rmax = fmaxf(rmax, fmaxf(bf_lo(sc), bf_hi(sc)));
                }
                pdst += 128;
                if (++s == NS) { s = 0; ph ^= 1; }
            }
        }
        {
#pragma unroll
            for (int o = 16; o; o >>= 1) rmax = fmaxf(rmax, __shfl_xor_sync(0xffffffffu, rmax, o));
            if (lane == 0) sts32f(sb + SM_STAT + warp * 4, rmax);
            bar_sync(1, 128);
            const uint4 mx = lds128(sb + SM_STAT);
            const float m = fmaxf(fmaxf(__uint_as_float(mx.x), __uint_as_float(mx.y)),
                                  fmaxf(__uint_as_float(mx.z), __uint_as_float(mx.w)));
            float e[32];
            float sum = 0.f;
#pragma unroll
            for (int i = 0; i < 4; i++) {
                const uint4 w = lds128(sb + SM_P + (i * 128 + tid) * 16);
                const uint32_t ww[4] = {w.x, w.y, w.z, w.w};
#pragma unroll
                for (int j = 0; j < 4; j++) {
                    e[i * 8 + 2 * j] = __expf(bf_lo(ww[j]) - m);
                    e[i * 8 + 2 * j + 1] = __expf(bf_hi(ww[j]) - m);
                    sum += e[i * 8 + 2 * j] + e[i * 8 + 2 * j + 1];
                }
            }
#pragma unroll
            for (int o = 16; o; o >>= 1) sum += __shfl_xor_sync(0xffffffffu, sum, o);
            if (lane == 0) sts32f(sb + SM_STAT + 16 + warp * 4, sum);
            bar_sync(1, 128);
            const uint4 sm = lds128(sb + SM_STAT + 16);
            const float inv = 1.f / ((__uint_as_float(sm.x) + __uint_as_float(sm.y)) +
                                     (__uint_as_float(sm.z) + __uint_as_float(sm.w)));
#pragma unroll
            for (int i = 0; i < 4; i++) {
                uint4 w;
                w.x = pack_bf(e[i * 8 + 0] * inv, e[i * 8 + 1] * inv);
                w.y = pack_bf(e[i * 8 + 2] * inv, e[i * 8 + 3] * inv);
                w.z = pack_bf(e[i * 8 + 4] * inv, e[i * 8 + 5] * inv);
                w.w = pack_bf(e[i * 8 + 6] * inv, e[i * 8 + 7] * inv);
                sts128(sb + SM_P + (i * 128 + tid) * 16, w);
            }
            bar_sync(1, 128);
        }
        {
            uint32_t off[4];
#pragma unroll
            for (int i = 0; i < 4; i++)
                off[i] = sb + SM_RING + ((mi >> 1) * 8 + r) * 512 + warp * 128 + (((2 * i + (mi & 1)) ^ r) << 4);
            const uint32_t pmask = t == (g >> 1) ? ((g & 1) ? 0xffff0000u : 0x0000ffffu) : 0u;
            uint32_t* odst = gx->o + ((c & 15) * 8 + (c >> 4)) * 128 + (warp * 2 + (t >> 1)) * 16 + (g >> 1) * 4 +
                             (t & 1) * 2 + (g & 1);
            uint32_t lane2;
            asm volatile("mov.u32 %0, %%laneid;" : "=r"(lane2));
#pragma unroll 1
            for (int pass = 0; pass < 2; pass++) {
                int n = pass * NCH;
                asm volatile("" : "+r"(n));
                float acc[4][4] = {};
                uint32_t psrc = sb + SM_P + t * 32;
                uint32_t va[8][4], vb[8][4] = {};
                uint32_t pt[4] = {};
                uint32_t cur[4];
#pragma unroll
                for (int j = 0; j < 4; j++) cur[j] = off[j] + s * CHUNK;
                uint32_t bar = sb + BAR_FULL + 8 * s, ready = 0;
#pragma unroll 1
                for (int i = n; i > 0; i--) {
                    if (!ready) mbar_wait(bar, ph);
                    const bool wrap = bar == sb + BAR_FULL + 8 * (NS - 1);
                    const uint32_t barn = wrap ? sb + BAR_FULL : bar + 8;
                    ph ^= wrap;
                    const uint4 p0 = lds128(psrc), p1 = lds128(psrc + 16);
#pragma unroll
                    for (int j = 0; j < 2; j++) ldsm4t(va[j], cur[j & 3] + (j >> 2) * 8192);
                    uint32_t tok;
                    asm volatile("{\n.reg .pred p;\nmbarrier.test_wait.parity.shared::cta.b64 p, [%2], %3;\n"
                                 "selp.u32 %0, 1, 0, p;\nselp.u32 %1, %4, %5, p;\n}"
                                 : "=r"(ready), "=r"(tok) : "r"(barn), "r"(ph), "r"(lane), "r"(lane2) : "memory");
#pragma unroll
                    for (int j = 2; j < 8; j++) ldsm4t(va[j], cur[j & 3] + (j >> 2) * 8192);
#pragma unroll
                    for (int j = 0; j < 8; j++) mma(acc[j & 3], vb[j], pt[(j >> 2) * 2], pt[(j >> 2) * 2 + 1]);
#pragma unroll
                    for (int j = 0; j < 8; j++) ldsm4t(vb[j], cur[j & 3] + (2 + (j >> 2)) * 8192);
                    asm volatile("{\n.reg .pred p;\nsetp.eq.u32 p, %1, 0;\n@p mbarrier.arrive.shared::cta.b64 _, [%0];\n}"
                                 ::"r"(bar + 8 * NS), "r"(tok) : "memory");
                    mma(acc[0], va[0], p0.x & pmask, p0.y & pmask);
                    mma(acc[1], va[1], p0.x & pmask, p0.y & pmask);
                    mma(acc[2], va[2], p0.x & pmask, p0.y & pmask);
                    mma(acc[3], va[3], p0.x & pmask, p0.y & pmask);
                    mma(acc[0], va[4], p0.z & pmask, p0.w & pmask);
                    mma(acc[1], va[5], p0.z & pmask, p0.w & pmask);
                    mma(acc[2], va[6], p0.z & pmask, p0.w & pmask);
                    mma(acc[3], va[7], p0.z & pmask, p0.w & pmask);
                    pt[0] = p1.x & pmask;
                    pt[1] = p1.y & pmask;
                    pt[2] = p1.z & pmask;
                    pt[3] = p1.w & pmask;
                    psrc += 128;
                    bar = barn;
                    const uint32_t step = wrap ? -(NS - 1) * CHUNK : CHUNK;
#pragma unroll
                    for (int j = 0; j < 4; j++) cur[j] += step;
                }
#pragma unroll
                for (int j = 0; j < 8; j++) mma(acc[j & 3], vb[j], pt[(j >> 2) * 2], pt[(j >> 2) * 2 + 1]);
                float ev[4], od[4];
#pragma unroll
                for (int T = 0; T < 4; T++) {
                    ev[T] = acc[T][0] + acc[T][3];
                    od[T] = acc[T][1] + acc[T][2];
                }
                ev[0] += __shfl_xor_sync(0xffffffffu, ev[1], 1);
                od[0] += __shfl_xor_sync(0xffffffffu, od[1], 1);
                ev[2] += __shfl_xor_sync(0xffffffffu, ev[3], 1);
                od[2] += __shfl_xor_sync(0xffffffffu, od[3], 1);
                ev[0] += __shfl_xor_sync(0xffffffffu, ev[2], 2);
                od[0] += __shfl_xor_sync(0xffffffffu, od[2], 2);
                const float other = __shfl_xor_sync(0xffffffffu, (g & 1) ? ev[0] : od[0], 4);
                const uint32_t w = (g & 1) ? pack_bf(other, od[0]) : pack_bf(ev[0], other);
                xst32(odst, n ? w : EMPTY);
                __syncwarp();
                if (!n && lane == 0) mbar_arrive(sb + BAR_DRY);
                if (c < 112) {
                    bar_sync(1, 128);
                    if (tid == 0) {
                        const bool f1 = c < 56;
                        const uint32_t on = n ? 0xffffffffu : 0u;
                        mbar_wait(sb + BAR_W0, ~on & 1);
                        l2_prefetch(p.w1 + c * 7168, 14336, on);
                        spin((f1 ? W1_DELAY : PF_DELAY) & on);
                        if (!f1) {
                            l2_prefetch(p.w2 + (c - 56) * 14336, 28672, on);
                            mbar_wait(sb + BAR_E1, ~on & 1);
                            spin(W2_DELAY & on);
                        }
                        tile_loads(sb + (n ? SM_WX : SM_WO + 8192), f1 ? &p.map_w1 : &p.map_w2, f1 ? c * 32 : ((c - 56) % 28) * 16,
                                   n ? 0 : 1 << 20, f1 ? 64 : 224, f1 ? 4096 : 7168, sb + (n ? BAR_W1 : BAR_X), n ? 8 - f1 : 1);
                    }
                }
            }
        }
    } else {
        const int ew = warp - 5, et = tid - 160;
        const int r = lane & 7, mi = lane >> 3;
        {
            uint32_t w[7];
#pragma unroll
            for (int i = 0; i < 7; i++)
                asm volatile("ld.global.nc.u32 %0, [%1];" : "=r"(w[i]) : "l"((const uint32_t*)p.x + ew * 224 + i * 32 + lane));
            __syncthreads();
            layernorm_row(w, sb + SM_XN + ew * 912, lane);
            mbar_wait(sb + BAR_WQ, 0);
            uint32_t a[8][4];
            frags_w448(a, sb + SM_WQ, ew, lane);
            const float2 q = gemv448(a, sb, ew, lane, et);
            if (et < 128) {
                xst32(gx->q + ((et >> 4) * 16 + (c >> 3)) * 128 + (c & 7) * 16 + (et & 15), ~pack_bf(q.x, q.y));
                asm volatile("bar.arrive 3, 256;" ::: "memory");
            }
        }
        const int hh = c / 7, jj = c - hh * 7;
        const bool is_f1 = c < 56;
        const int cg = (c - 56) % 28, half = (c - 56) / 28;
        const int ht0 = (c - 112) * 7 + min(ew, 6);
        uint32_t side;
        asm volatile("ld.global.nc.u32 %0, [%1];" : "=r"(side)
                     : "l"(is_f1 ? p.b1 + c * 32 + (et & 15) * 2
                           : c < 112 ? p.b2 + cg * 16 + r * 2
                           : p.x + ((ht0 & 6) + (mi & 1)) * DM + (ht0 >> 3) * 32 + (r & 3) * 8 + (ht0 & 1) * 4 + (r >> 2) * 2));
        uint32_t seen_prog = 0;
#pragma unroll 1
        for (int pass = 0; pass < 2; pass++) {
            uint32_t live = pass;
            asm volatile("" : "+r"(live));
            const uint32_t want = 0u - live, wipe = ~want;
            const int et = pin(tid - 160), ew = et >> 5, lane = et & 31;
            const int g = lane >> 2, t = lane & 3, r = lane & 7, mi = lane >> 3;
            if (et == 0) {
                if (!live) mbar_wait(sb + BAR_Q, 0);
#pragma unroll 1
                for (int it = 0; it < SPIN_LIMIT; it++) {
                    const uint32_t prog = ctl_load(sb + SM_PROG);
                    int total = 0;
                    if (prog == seen_prog) __nanosleep(100);
                    if (prog != seen_prog || prog >= 2 * NCH - 8)
                        asm volatile("ld.relaxed.gpu.global.u32 %0, [%1];" : "=r"(total) : "l"(gx->count + 32) : "memory");
                    if (total >= ALL_CHUNKS - LIFT_LEFT) {
                        ctl_store(sb + SM_DEPTH, NS);
                    } else if (prog != seen_prog) {
                        const int lead = prog * NCTA - total;
                        ctl_store(sb + SM_DEPTH, lead >= LEAD1 ? 1 : lead >= LEAD2 ? 2 : lead >= LEAD2 - 128 ? 3 : lead >= LEAD2 - 256 ? 4 : NS);
                    }
                    seen_prog = prog;
                    if (live ? total >= ALL_CHUNKS - TRIG_LEFT : mbar_test(sb + BAR_DRY, 0)) break;
                }
                tile_loads(sb + SM_WO, &p.map_wo, jj * 64, live ? hh * 256 : 1 << 20, 32, 4096, sb + (live ? BAR_WO : BAR_X + 8),
                           c >= 112 ? 0 : live ? 8 : 1);
            } else if (et == 32 && live) {
                uint32_t seen;
                mbar_wait(sb + BAR_DRY, 0);
                asm volatile("atom.release.gpu.global.add.u32 %0, [%1], 1;" : "=r"(seen) : "l"(gx->count) : "memory");
                int it = 0;
                for (seen++; seen < NCTA && ++it < SPIN_LIMIT;) {
                    __nanosleep(512);
                    asm volatile("ld.relaxed.gpu.global.u32 %0, [%1];" : "=r"(seen) : "l"(gx->count) : "memory");
                }
                asm volatile("ld.acquire.gpu.global.u32 %0, [%1];" : "=r"(seen) : "l"(gx->count) : "memory");
            }
            __syncwarp();
            bar_sync(2, 256);
            if (c >= 112) {
                if (ew < 7) {
                    const bool odd = mi & 1;
                    const int ht = (c - 112) * 7 + ew;
                    float a0, a1;
                    uint32_t* const dst = gx->h + pin((((mi >> 1) * 14 + (ht >> 3)) * 8 + (ht & 6) + (mi & 1)) * 16 + (ht & 1) * 8 + r);
                    Poll<4, 128> in(gx->part + pin(ht * 512 + lane * 4), want, want);
                    in.finish([&] {
                        const uint4 (&v)[4] = in.v;
                        const float f0 = (__uint_as_float(v[0].x) + __uint_as_float(v[1].x)) + (__uint_as_float(v[2].x) + __uint_as_float(v[3].x));
                        const float f1 = (__uint_as_float(v[0].y) + __uint_as_float(v[1].y)) + (__uint_as_float(v[2].y) + __uint_as_float(v[3].y));
                        const float f2 = (__uint_as_float(v[0].z) + __uint_as_float(v[1].z)) + (__uint_as_float(v[2].z) + __uint_as_float(v[3].z));
                        const float f3 = (__uint_as_float(v[0].w) + __uint_as_float(v[1].w)) + (__uint_as_float(v[2].w) + __uint_as_float(v[3].w));
                        a0 = (odd ? f1 : f0) + __shfl_xor_sync(0xffffffffu, odd ? f0 : f1, 8);
                        a1 = (odd ? f3 : f2) + __shfl_xor_sync(0xffffffffu, odd ? f2 : f3, 8);
                    });
                    a0 += __shfl_xor_sync(0xffffffffu, a0, 16);
                    a1 += __shfl_xor_sync(0xffffffffu, a1, 16);
                    xst32(dst, bf2_add(side, pack_bf(a0, a1)) | wipe);
                }
                if (!live) bar_sync(5, 256);
                continue;
            }
            {
                uint32_t fa[4];
#pragma unroll
                for (int mt = 0; mt < 4; mt++)
                    fa[mt] = pin(sb + SM_WO + (ew * 32 + (mi >> 1) * 8 + r) * 128 + (((2 * mt + (mi & 1)) ^ r) << 4));
                const uint32_t wb = pin(sb + SM_RED + (ew * 544 + t * 136 + g * 2) * 4);
                const uint32_t rb = pin(sb + SM_RED + ((ew & 3) * 136 + ((ew >> 2) * 32 + (r >> 1) * 8 + mi * 2 + (r & 1)) * 2) * 4);
                uint32_t* const pdst = gx->part + pin((((jj * 8 + ew) * 2 + (lane >> 4)) * 16 + hh) * 32 + (lane & 15) * 2);
                Poll<1, 0> in(gx->o + pin((hh * 8 + g) * 128 + ew * 16 + t * 4), want, want);
                in.until(sb + BAR_WO + 8 * ew);
                uint32_t a[8][4];
#pragma unroll
                for (int mt = 0; mt < 4; mt++) ldsm4t(a[mt], fa[mt]);
#pragma unroll
                for (int mt = 0; mt < 4; mt++) ldsm4t(a[4 + mt], fa[mt] + 2048);
                float acc[4][4];
                in.finish([&] {
#pragma unroll
                    for (int mt = 0; mt < 4; mt++) mma0(acc[mt], a[mt], in.v[0].x, in.v[0].y);
#pragma unroll
                    for (int mt = 0; mt < 4; mt++) mma(acc[mt], a[4 + mt], in.v[0].z, in.v[0].w);
                });
#pragma unroll
                for (int mt = 0; mt < 4; mt++) {
                    sts64f(wb + mt * 128, acc[mt][0], acc[mt][1]);
                    sts64f(wb + mt * 128 + 64, acc[mt][2], acc[mt][3]);
                }
                bar_sync(2, 256);
                float2 v[8];
#pragma unroll
                for (int w = 0; w < 8; w++) v[w] = lds64f(rb + w * 2176);
                const float s0 = ((v[0].x + v[1].x) + (v[2].x + v[3].x)) + ((v[4].x + v[5].x) + (v[6].x + v[7].x));
                const float s1 = ((v[0].y + v[1].y) + (v[2].y + v[3].y)) + ((v[4].y + v[5].y) + (v[6].y + v[7].y));
                xst64(pdst, __float_as_uint(s0) | wipe, __float_as_uint(s1) | wipe);
            }
            if (et == 0 && live) mbar_arrive(sb + BAR_E1);
            const uint32_t wbar = sb + BAR_W1 + 8 * ew;
            if (is_f1) {
                constexpr uint32_t ONES = 0x3f803f80u;
                if (ew < 7) {
                    const int b = (et >> 4) & 7, pr = et & 15;
                    const uint32_t fa = pin(sb + SM_WX + (ew * 64 + (mi >> 1) * 8 + r) * 64 + (((mi & 1) ^ (r >> 1)) << 4));
                    const uint32_t wb = pin(sb + SM_RED + (ew * 288 + t * 72 + g) * 4);
                    const uint32_t sw = pin(sb + SM_RED + (ew * 288 + g * 36 + (t == (g >> 1) ? 32 : 34)) * 4);
                    const uint32_t rs = pin(sb + SM_RED + b * 144 + 128), rz = pin(sb + SM_RED + b * 144 + pr * 8);
                    const uint32_t cw = pin(sb + SM_XN + (ew * 32 + g + (t >> 1) * 16 + (t & 1) * 8) * 4), cr = pin(sb + SM_XN + pr * 8);
                    const bool odd = pin(g & 1);
                    uint32_t* const dst = gx->r + pin((((b >> 2) * 56 + c) * 4 + (b & 3)) * 16 + (pr & 3) * 4 + (pr >> 2));
                    Poll<2, 128> in(gx->h + pin(((c & 1) * 14 + ew * 2) * 128 + lane * 4), want, want);
                    mbar_wait(wbar, wipe & 1);
                    uint32_t a[8][4];
#pragma unroll
                    for (int ks = 0; ks < 4; ks++) {
                        ldsm4t(a[ks * 2], fa + ks * 1024);
                        ldsm4t(a[ks * 2 + 1], (fa ^ 32) + ks * 1024);
                    }
                    float cs[2][4] = {}, z[2][4], st[4];
#pragma unroll
                    for (int ks = 0; ks < 4; ks++) {
                        mma(cs[0], a[ks * 2], ONES, ONES);
                        mma(cs[1], a[ks * 2 + 1], ONES, ONES);
                    }
                    sts32f(cw, (t & 1) ? ((t & 2) ? cs[1][2] : cs[0][2]) : ((t & 2) ? cs[1][0] : cs[0][0]));
                    bar_sync(4, 224);
                    float2 cv[7];
#pragma unroll
                    for (int w = 0; w < 7; w++) cv[w] = lds64f(cr + w * 128);
                    const float cs0 = ((cv[0].x + cv[1].x) + (cv[2].x + cv[3].x)) + ((cv[4].x + cv[5].x) + cv[6].x);
                    const float cs1 = ((cv[0].y + cv[1].y) + (cv[2].y + cv[3].y)) + ((cv[4].y + cv[5].y) + cv[6].y);
                    const auto step = [&](int ks) {
                        const uint4& x = in.v[ks >> 1];
                        const uint32_t b0 = (ks & 1) ? x.z : x.x, b1 = (ks & 1) ? x.w : x.y;
                        const uint32_t sa[4] = {b0, ONES, b1, ONES};
                        if (ks == 0) {
                            mma0(st, sa, b0, b1);
                            mma0(z[0], a[0], b0, b1);
                            mma0(z[1], a[1], b0, b1);
                        } else {
                            mma(st, sa, b0, b1);
                            mma(z[0], a[ks * 2], b0, b1);
                            mma(z[1], a[ks * 2 + 1], b0, b1);
                        }
                    };
                    in.finish([&] {
                        step(0);
                        step(1);
                    });
                    step(2);
                    step(3);
                    sts64f(sw, odd ? st[3] : st[2], odd ? st[1] : st[0]);
#pragma unroll
                    for (int mt = 0; mt < 2; mt++) {
                        sts32f(wb + mt * 64, z[mt][0]);
                        sts32f(wb + mt * 64 + 144, z[mt][1]);
                        sts32f(wb + mt * 64 + 32, z[mt][2]);
                        sts32f(wb + mt * 64 + 176, z[mt][3]);
                    }
                    bar_sync(4, 224);
                    if (ew < 4) {
                        float2 sv[7], zv[7];
#pragma unroll
                        for (int w = 0; w < 7; w++) sv[w] = lds64f(rs + w * 1152);
#pragma unroll
                        for (int w = 0; w < 7; w++) zv[w] = lds64f(rz + w * 1152);
                        const float mu = (((sv[0].x + sv[1].x) + (sv[2].x + sv[3].x)) + ((sv[4].x + sv[5].x) + sv[6].x)) * (1.f / DM);
                        const float sq = ((sv[0].y + sv[1].y) + (sv[2].y + sv[3].y)) + ((sv[4].y + sv[5].y) + sv[6].y);
                        const float inv = inv_std(bf_round(fmaxf(fmaf(sq, 1.f / DM, -mu * mu), 0.f)));
                        const float mean = bf_round(mu);
                        const float z0 = ((zv[0].x + zv[1].x) + (zv[2].x + zv[3].x)) + ((zv[4].x + zv[5].x) + zv[6].x);
                        const float z1 = ((zv[0].y + zv[1].y) + (zv[2].y + zv[3].y)) + ((zv[4].y + zv[5].y) + zv[6].y);
                        const uint32_t u = pack_bf(fmaf(-mean, cs0, z0) * inv, fmaf(-mean, cs1, z1) * inv);
                        xst32(dst, bf2_relu_sq(bf2_add(u, side)) | wipe);
                    }
                }
            } else {
                const uint32_t fa = pin(sb + SM_WX + (ew * 224 + (mi >> 1) * 8 + r) * 32 + (((mi & 1) ^ (r >> 2)) << 4));
                const uint32_t wb = pin(sb + SM_XN + (ew * 160 + (t & 1) * 80 + (g >> 1) * 4 + (t >> 1) * 2 + (g & 1)) * 4);
                const uint32_t rb = pin(sb + SM_XN + (mi * 40 + r * 4) * 4);
                const bool upper = pin(t >> 1);
                uint32_t* const dst = (live ? (uint32_t*)p.out : gx->sink) + pin((half * 4 + mi) * 224 + cg * 8 + r);
                Poll<4, 128, true> in(gx->r + pin((half * 56 + ew * 7) * 64 + lane * 4), want, lane < 16 ? want : 0u,
                                      gx->h + pin((((c & 1) * 14 + (cg >> 1)) * 8 + half * 4 + mi) * 16 + (r & 3) * 4 +
                                                  (cg & 1) * 2 + (r >> 2)),
                                      ew == 0 ? want : 0u);
                mbar_wait(wbar, wipe & 1);
                uint32_t a[14][4];
#pragma unroll
                for (int ks = 0; ks < 14; ks++) ldsm4t(a[ks], fa + ks * 512);
                float acc[4][4];
                const auto step = [&](int i) {
                    mma(acc[0], a[4 * i], in.v[i].x, in.v[i].y);
                    mma(acc[1], a[4 * i + 1], in.v[i].z, in.v[i].w);
                    if (i < 3) {
                        mma(acc[2], a[4 * i + 2], in.v[i].x, in.v[i].y);
                        mma(acc[3], a[4 * i + 3], in.v[i].z, in.v[i].w);
                    }
                };
                in.finish([&] {
                    mma0(acc[0], a[0], in.v[0].x, in.v[0].y);
                    mma0(acc[1], a[1], in.v[0].z, in.v[0].w);
                    mma0(acc[2], a[2], in.v[0].x, in.v[0].y);
                    mma0(acc[3], a[3], in.v[0].z, in.v[0].w);
                    step(1);
                });
                step(2);
                step(3);
                sts32f(wb, upper ? acc[2][0] + acc[3][0] : acc[0][0] + acc[1][0]);
                sts32f(wb + 160, upper ? acc[2][1] + acc[3][1] : acc[0][1] + acc[1][1]);
                sts32f(wb + 64, upper ? acc[2][2] + acc[3][2] : acc[0][2] + acc[1][2]);
                sts32f(wb + 224, upper ? acc[2][3] + acc[3][3] : acc[0][3] + acc[1][3]);
                if (ew == 0) {
                    bar_sync(2, 256);
                    float x[8], y[8];
#pragma unroll
                    for (int w = 0; w < 8; w++) {
                        const uint4 q = lds128(rb + w * 640);
                        x[w] = __uint_as_float(q.x) + __uint_as_float(q.z);
                        y[w] = __uint_as_float(q.y) + __uint_as_float(q.w);
                    }
                    const float s0 = ((x[0] + x[1]) + (x[2] + x[3])) + ((x[4] + x[5]) + (x[6] + x[7]));
                    const float s1 = ((y[0] + y[1]) + (y[2] + y[3])) + ((y[4] + y[5]) + (y[6] + y[7]));
                    *dst = bf2_add(in.word, bf2_add(pack_bf(s0, s1), side));
                } else {
                    asm volatile("bar.arrive 2, 256;" ::: "memory");
                    if (c == 56 && et == 32 && live) {
                        xst32(gx->count, 0);
                        xst32(gx->count + 32, 0);
                    }
                }
            }
            if (!live) bar_sync(5, 256);
        }
    }
}

using EncodeFn = CUresult (*)(CUtensorMap*, CUtensorMapDataType, cuuint32_t, void*, const cuuint64_t*, const cuuint64_t*,
                              const cuuint32_t*, const cuuint32_t*, CUtensorMapInterleave, CUtensorMapSwizzle,
                              CUtensorMapL2promotion, CUtensorMapFloatOOBfill);

void encode_map(EncodeFn fn, CUtensorMap* map, const void* base, int rows, int cols, int box_rows, int box_cols,
                CUtensorMapSwizzle swizzle) {
    const cuuint64_t dims[2] = {(cuuint64_t)cols, (cuuint64_t)rows};
    const cuuint64_t strides[1] = {(cuuint64_t)cols * 2};
    const cuuint32_t box[2] = {(cuuint32_t)box_cols, (cuuint32_t)box_rows};
    const cuuint32_t steps[2] = {1, 1};
    fn(map, CU_TENSOR_MAP_DATA_TYPE_BFLOAT16, 2, const_cast<void*>(base), dims, strides, box, steps,
       CU_TENSOR_MAP_INTERLEAVE_NONE, swizzle, CU_TENSOR_MAP_L2_PROMOTION_L2_128B, CU_TENSOR_MAP_FLOAT_OOB_FILL_NONE);
}

}

extern "C" void kernel_launch(void* const* d_in, const int* in_sizes, int n_in, void* d_out, int out_size) {
    (void)in_sizes; (void)n_in; (void)out_size;
    Params p;
    p.x = (const __nv_bfloat16*)d_in[0];
    p.k = (const __nv_bfloat16*)d_in[1];
    p.v = (const __nv_bfloat16*)d_in[2];
    p.wq = (const __nv_bfloat16*)d_in[3];
    p.wo = (const __nv_bfloat16*)d_in[4];
    p.w1 = (const __nv_bfloat16*)d_in[6];
    p.b1 = (const __nv_bfloat16*)d_in[7];
    p.w2 = (const __nv_bfloat16*)d_in[8];
    p.b2 = (const __nv_bfloat16*)d_in[9];
    p.out = (__nv_bfloat16*)d_out;
    cudaGetSymbolAddress((void**)&p.xch, g_x);
    void* fn = nullptr;
    cudaDriverEntryPointQueryResult found;
    cudaGetDriverEntryPoint("cuTensorMapEncodeTiled", &fn, cudaEnableDefault, &found);
    encode_map((EncodeFn)fn, &p.map_wo, p.wo, NH * DH, DM, 32, 64, CU_TENSOR_MAP_SWIZZLE_128B);
    encode_map((EncodeFn)fn, &p.map_w1, p.w1, DM, FF, 64, 32, CU_TENSOR_MAP_SWIZZLE_64B);
    encode_map((EncodeFn)fn, &p.map_w2, p.w2, FF, DM, 224, 16, CU_TENSOR_MAP_SWIZZLE_32B);
    cudaFuncSetAttribute(fused_decode_kernel, cudaFuncAttributeMaxDynamicSharedMemorySize, SM_TOTAL);
    fused_decode_kernel<<<NCTA, NTHREADS, SM_TOTAL>>>(p);
}
```

```cpp
#include <cuda.h>
#include <cuda_runtime.h>
#include <cuda_bf16.h>
#include <stdint.h>

namespace {

constexpr int DM = 448, NH = 16, SK = 4096, DH = 256, FF = 1792;
constexpr int NCTA = 128;
constexpr int CHUNK = 32768;
constexpr int NCH = SK / 64;
constexpr int NS = 5;
constexpr int ALL_CHUNKS = NCTA * 2 * NCH;
constexpr int LEAD1 = 128;
constexpr int LEAD2 = -128;
constexpr int LIFT_LEFT = 370;
constexpr int TRIG_LEFT = 220;
constexpr int K1_DELAY = 2000;
constexpr int W1_DELAY = 600;
constexpr int PF_DELAY = 500;
constexpr int W2_DELAY = 600;
constexpr int ROT = 32;
constexpr int NTHREADS = 13 * 32;
constexpr int SPIN_LIMIT = 1 << 18;
constexpr int WAIT_LIMIT = 1 << 14;

constexpr int SM_RING = 0;
constexpr int SM_WX = 0;
constexpr int SM_WQ = NS * CHUNK;
constexpr int SM_WO = SM_WQ;
constexpr int SM_P = SM_WQ + 32768;
constexpr int SM_RED = SM_P + 8192;
constexpr int SM_XN = SM_RED + 4 * 544 * 4;
constexpr int SM_Q = SM_XN + 8 * 456 * 2;
constexpr int SM_STAT = SM_Q + 512;
constexpr int SM_PROG = SM_STAT + 32, SM_DEPTH = SM_STAT + 36;
constexpr int SM_BAR = SM_STAT + 64;
constexpr int BAR_FULL = SM_BAR, BAR_EMPTY = BAR_FULL + 8 * NS, BAR_WO = BAR_EMPTY + 8 * NS, BAR_DRY = BAR_WO + 32,
              BAR_WQ = BAR_DRY + 8, BAR_Q = BAR_WQ + 8, BAR_W0 = BAR_WO + 24, BAR_E1 = BAR_Q + 8, BAR_X = BAR_E1 + 8,
              BAR_W1 = BAR_X + 16;
constexpr int SM_TOTAL = BAR_W1 + 64;
static_assert(SM_TOTAL <= 232448, "shared memory budget");

struct Exchange {
    uint32_t q[NCTA * 128];
    uint32_t o[NH * 8 * 128];
    uint32_t part[14 * 8 * 16 * 32];
    uint32_t h[2 * 14 * 8 * 16];
    uint32_t r[2 * 56 * 4 * 16];
    uint32_t count[64];
    uint32_t sink[8 * 224];
};
__device__ __align__(128) Exchange g_x;

__device__ __forceinline__ void mbar_init(uint32_t bar, uint32_t count) {
    asm volatile("mbarrier.init.shared::cta.b64 [%0], %1;" ::"r"(bar), "r"(count) : "memory");
}
__device__ __forceinline__ void mbar_arrive(uint32_t bar) {
    asm volatile("mbarrier.arrive.shared::cta.b64 _, [%0];" ::"r"(bar) : "memory");
}
__device__ __forceinline__ void mbar_expect_tx(uint32_t bar, uint32_t bytes) {
    asm volatile("mbarrier.arrive.expect_tx.shared::cta.b64 _, [%0], %1;" ::"r"(bar), "r"(bytes) : "memory");
}
__device__ __forceinline__ void mbar_wait(uint32_t bar, uint32_t parity) {
    asm volatile("{\n.reg .pred p, q;\n.reg .u32 n;\nmov.u32 n, %2;\n"
                 "RETRY:\nsub.u32 n, n, 1;\nsetp.ne.u32 q, n, 0;\n"
                 "mbarrier.try_wait.parity.shared::cta.b64 p, [%0], %1;\nand.pred q, q, !p;\n@q bra RETRY;\n}"
                 ::"r"(bar), "r"(parity), "n"(WAIT_LIMIT) : "memory");
}
__device__ __forceinline__ uint32_t mbar_test(uint32_t bar, uint32_t parity) {
    uint32_t done;
    asm volatile("{\n.reg .pred p;\nmbarrier.test_wait.parity.shared::cta.b64 p, [%1], %2;\nselp.u32 %0, 1, 0, p;\n}"
                 : "=r"(done) : "r"(bar), "r"(parity) : "memory");
    return done;
}
__device__ __forceinline__ void spin(uint32_t cycles) {
    const uint32_t t0 = (uint32_t)clock();
    do {
    } while ((uint32_t)clock() - t0 < cycles);
}
__device__ __forceinline__ void spin_or(uint32_t cycles, uint32_t bar) {
    const uint32_t t0 = (uint32_t)clock();
    do {
    } while (!mbar_test(bar, 0) && (uint32_t)clock() - t0 < cycles);
}
__device__ __forceinline__ void l2_prefetch(const void* src, uint32_t bytes, uint32_t on) {
    asm volatile("{\n.reg .pred p;\nsetp.ne.u32 p, %2, 0;\n@p cp.async.bulk.prefetch.L2.global [%0], %1;\n}"
                 ::"l"(src), "r"(bytes), "r"(on) : "memory");
}
__device__ __forceinline__ void bulk_load(uint32_t dst, const void* src, uint32_t bytes, uint32_t bar, uint64_t pol) {
    asm volatile("cp.async.bulk.shared::cluster.global.mbarrier::complete_tx::bytes.L2::cache_hint [%0], [%1], %2, [%3], %4;"
                 ::"r"(dst), "l"(src), "r"(bytes), "r"(bar), "l"(pol) : "memory");
}
__device__ __forceinline__ void tile_loads(uint32_t dst, const CUtensorMap* map, int col, int row, int rows, uint32_t bytes,
                                           uint32_t bar, int n) {
#pragma unroll 1
    for (int i = 0; i < n; i++, dst += bytes, row += rows, bar += 8) {
        mbar_expect_tx(bar, bytes);
        asm volatile("cp.async.bulk.tensor.2d.shared::cluster.global.mbarrier::complete_tx::bytes [%0], [%1, {%2, %3}], [%4];"
                     ::"r"(dst), "l"(map), "r"(col), "r"(row), "r"(bar) : "memory");
    }
}
__device__ __forceinline__ void bar_sync(int id, int n) { asm volatile("bar.sync %0, %1;" ::"r"(id), "r"(n) : "memory"); }

__device__ __forceinline__ void ldsm4(uint32_t (&r)[4], uint32_t a) {
    asm volatile("ldmatrix.sync.aligned.m8n8.x4.shared.b16 {%0,%1,%2,%3}, [%4];"
                 : "=r"(r[0]), "=r"(r[1]), "=r"(r[2]), "=r"(r[3]) : "r"(a) : "memory");
}
__device__ __forceinline__ void ldsm4t(uint32_t (&r)[4], uint32_t a) {
    asm volatile("ldmatrix.sync.aligned.m8n8.x4.trans.shared.b16 {%0,%1,%2,%3}, [%4];"
                 : "=r"(r[0]), "=r"(r[1]), "=r"(r[2]), "=r"(r[3]) : "r"(a) : "memory");
}
__device__ __forceinline__ void mma(float (&c)[4], const uint32_t (&a)[4], uint32_t b0, uint32_t b1) {
    asm volatile("mma.sync.aligned.m16n8k16.row.col.f32.bf16.bf16.f32 {%0,%1,%2,%3}, {%4,%5,%6,%7}, {%8,%9}, {%0,%1,%2,%3};"
                 : "+f"(c[0]), "+f"(c[1]), "+f"(c[2]), "+f"(c[3])
                 : "r"(a[0]), "r"(a[1]), "r"(a[2]), "r"(a[3]), "r"(b0), "r"(b1));
}
__device__ __forceinline__ void mma0(float (&c)[4], const uint32_t (&a)[4], uint32_t b0, uint32_t b1) {
    asm volatile("mma.sync.aligned.m16n8k16.row.col.f32.bf16.bf16.f32 {%0,%1,%2,%3}, {%4,%5,%6,%7}, {%8,%9}, {%10,%10,%10,%10};"
                 : "=f"(c[0]), "=f"(c[1]), "=f"(c[2]), "=f"(c[3])
                 : "r"(a[0]), "r"(a[1]), "r"(a[2]), "r"(a[3]), "r"(b0), "r"(b1), "f"(0.f));
}
__device__ __forceinline__ uint32_t lds32(uint32_t a) {
    uint32_t v;
    asm volatile("ld.shared.u32 %0, [%1];" : "=r"(v) : "r"(a) : "memory");
    return v;
}
__device__ __forceinline__ uint32_t ctl_load(uint32_t a) {
    uint32_t v;
    asm volatile("ld.volatile.shared.u32 %0, [%1];" : "=r"(v) : "r"(a) : "memory");
    return v;
}
__device__ __forceinline__ void ctl_store(uint32_t a, uint32_t v) {
    asm volatile("st.volatile.shared.u32 [%0], %1;" ::"r"(a), "r"(v) : "memory");
}
__device__ __forceinline__ float2 lds64f(uint32_t a) {
    float2 v;
    asm volatile("ld.shared.v2.f32 {%0,%1}, [%2];" : "=f"(v.x), "=f"(v.y) : "r"(a) : "memory");
    return v;
}
__device__ __forceinline__ uint4 lds128(uint32_t a) {
    uint4 v;
    asm volatile("ld.shared.v4.u32 {%0,%1,%2,%3}, [%4];" : "=r"(v.x), "=r"(v.y), "=r"(v.z), "=r"(v.w) : "r"(a) : "memory");
    return v;
}
__device__ __forceinline__ void sts16(uint32_t a, uint32_t v) {
    asm volatile("st.shared.u16 [%0], %1;" ::"r"(a), "h"((unsigned short)v) : "memory");
}
__device__ __forceinline__ void sts32(uint32_t a, uint32_t v) {
    asm volatile("st.shared.u32 [%0], %1;" ::"r"(a), "r"(v) : "memory");
}
__device__ __forceinline__ void sts32f(uint32_t a, float v) {
    asm volatile("st.shared.f32 [%0], %1;" ::"r"(a), "f"(v) : "memory");
}
__device__ __forceinline__ void sts64f(uint32_t a, float x, float y) {
    asm volatile("st.shared.v2.f32 [%0], {%1,%2};" ::"r"(a), "f"(x), "f"(y) : "memory");
}
__device__ __forceinline__ void sts128(uint32_t a, uint4 v) {
    asm volatile("st.shared.v4.u32 [%0], {%1,%2,%3,%4};" ::"r"(a), "r"(v.x), "r"(v.y), "r"(v.z), "r"(v.w) : "memory");
}

constexpr uint32_t EMPTY = 0xffffffffu;
__device__ __forceinline__ void xld32(uint32_t& v, const uint32_t* p, uint32_t empty) {
    asm volatile("{\n.reg .pred p;\nsetp.eq.u32 p, %0, %2;\n@p ld.relaxed.gpu.global.u32 %0, [%1];\n}"
                 : "+r"(v) : "l"(p), "r"(empty) : "memory");
}
__device__ __forceinline__ void xld128(uint4& v, const uint32_t* p, uint32_t top) {
    asm volatile("{\n.reg .pred p;\nsetp.eq.u32 p, %5, 0xffffffff;\n@p ld.relaxed.gpu.global.v4.u32 {%0,%1,%2,%3}, [%4];\n}"
                 : "+r"(v.x), "+r"(v.y), "+r"(v.z), "+r"(v.w) : "l"(p), "r"(top) : "memory");
}
__device__ __forceinline__ void xst32(uint32_t* p, uint32_t v) {
    asm volatile("st.relaxed.gpu.global.u32 [%0], %1;" ::"l"(p), "r"(v) : "memory");
}
__device__ __forceinline__ void xst64(uint32_t* p, uint32_t a, uint32_t b) {
    asm volatile("st.relaxed.gpu.global.v2.u32 [%0], {%1,%2};" ::"l"(p), "r"(a), "r"(b) : "memory");
}
__device__ __forceinline__ uint32_t top_word(const uint4& v) { return max(__vimax3_u32(v.x, v.y, v.z), v.w); }
template <int N, int STRIDE, bool WORD = false>
struct Poll {
    uint4 v[N];
    uint32_t top[N], word, want;
    const uint32_t *src, *wsrc;
    int left;
    __device__ __forceinline__ Poll(const uint32_t* s, uint32_t init, uint32_t init_last, const uint32_t* ws = nullptr,
                                    uint32_t init_word = 0)
        : word(init_word), want(init), src(s), wsrc(ws), left(init ? SPIN_LIMIT : 2) {
#pragma unroll
        for (int i = 0; i < N; i++) {
            top[i] = i == N - 1 ? init_last : init;
            v[i] = make_uint4(top[i], top[i], top[i], top[i]);
        }
    }
    __device__ __forceinline__ void issue() {
#pragma unroll
        for (int i = 0; i < N; i++) xld128(v[i], src + i * STRIDE, top[i]);
        if (WORD) xld32(word, wsrc, EMPTY);
        left--;
    }
    __device__ __forceinline__ bool missing() {
        uint32_t m = WORD ? word : 0;
#pragma unroll
        for (int i = 0; i < N; i++) {
            top[i] = top_word(v[i]);
            m = max(m, top[i]);
        }
        return __any_sync(0xffffffffu, m == want && left > 0);
    }
    __device__ __forceinline__ void until(uint32_t bar) {
#pragma unroll 1
        while (!mbar_test(bar, 0)) {
            issue();
            if (!missing()) break;
        }
        mbar_wait(bar, ~want & 1);
    }
    template <class F>
    __device__ __forceinline__ void finish(F use) {
        bool again;
#pragma unroll 1
        do {
            issue();
            again = missing();
            use();
        } while (again);
    }
};
__device__ __forceinline__ uint32_t poll32(const uint32_t* src, uint32_t init, uint32_t empty) {
    int left = SPIN_LIMIT;
#pragma unroll 1
    do {
        xld32(init, src, empty);
        left--;
    } while (__any_sync(0xffffffffu, init == empty && left > 0));
    return init;
}
__device__ __forceinline__ uint32_t pin(uint32_t v) {
    asm volatile("shfl.sync.bfly.b32 %0, %0, 0, 0x1f, 0xffffffff;" : "+r"(v));
    return v;
}
__device__ __forceinline__ uint32_t bf2_add(uint32_t a, uint32_t b) {
    uint32_t r;
    asm("add.rn.bf16x2 %0, %1, %2;" : "=r"(r) : "r"(a), "r"(b));
    return r;
}
__device__ __forceinline__ uint32_t bf2_relu_sq(uint32_t a) {
    uint32_t r;
    asm("{\n.reg .b32 m;\nmax.bf16x2 m, %1, %2;\nmul.rn.bf16x2 %0, m, m;\n}" : "=r"(r) : "r"(a), "r"(0));
    return r;
}

__device__ __forceinline__ uint32_t pack_bf(float lo, float hi) {
    uint32_t r;
    asm("cvt.rn.bf16x2.f32 %0, %1, %2;" : "=r"(r) : "f"(hi), "f"(lo));
    return r;
}
__device__ __forceinline__ float bf_round(float v) { return __uint_as_float(pack_bf(0.f, v)); }
__device__ __forceinline__ float bf_lo(uint32_t w) { return __uint_as_float(w << 16); }
__device__ __forceinline__ float bf_hi(uint32_t w) { return __uint_as_float(w & 0xffff0000u); }

__device__ __forceinline__ float inv_std(float var) {
    float sd, inv;
    asm("sqrt.approx.ftz.f32 %0, %1;" : "=f"(sd) : "f"(bf_round(var + 1e-5f)));
    asm("rcp.approx.ftz.f32 %0, %1;" : "=f"(inv) : "f"(bf_round(sd)));
    return inv;
}

__device__ __forceinline__ void layernorm_row(const uint32_t (&w)[7], uint32_t dst, int lane) {
    const float shift = bf_lo(__shfl_sync(0xffffffffu, w[0], 0));
    float s = 0.f, ss = 0.f;
#pragma unroll
    for (int i = 0; i < 7; i++) {
        const float a = bf_lo(w[i]) - shift, b = bf_hi(w[i]) - shift;
        s += a + b;
        ss = fmaf(a, a, fmaf(b, b, ss));
    }
#pragma unroll
    for (int o = 16; o; o >>= 1) {
        s += __shfl_xor_sync(0xffffffffu, s, o);
        ss += __shfl_xor_sync(0xffffffffu, ss, o);
    }
    const float md = s * (1.f / DM);
    const float mean = bf_round(shift + md);
    const float inv = inv_std(bf_round(fmaxf(ss * (1.f / DM) - md * md, 0.f)));
#pragma unroll
    for (int i = 0; i < 7; i++) {
        const float a = bf_round(bf_lo(w[i]) - mean) * inv, b = bf_round(bf_hi(w[i]) - mean) * inv;
        sts32(dst + (i * 32 + lane) * 4, pack_bf(a, b));
    }
}

__device__ __forceinline__ void frags_w448(uint32_t (&a)[8][4], uint32_t src, int ew, int lane) {
    const int r = lane & 7, mi = lane >> 3;
    const uint32_t base = src + ((ew < 7 ? ew : 0) * 64 + (mi >> 1) * 8 + r) * 64;
#pragma unroll
    for (int ks = 0; ks < 4; ks++)
#pragma unroll
        for (int mt = 0; mt < 2; mt++)
            ldsm4t(a[ks * 2 + mt], base + ks * 1024 + (((2 * mt + (mi & 1)) ^ (r >> 1)) << 4));
}
__device__ __forceinline__ float2 gemv448(const uint32_t (&a)[8][4], uint32_t sb, int ew, int lane, int et) {
    const int g = lane >> 2, t = lane & 3;
    bar_sync(2, 256);
    if (ew < 7) {
        float c[4][4] = {};
        const uint32_t xb = sb + SM_XN + (g * 228 + ew * 32 + t) * 4;
#pragma unroll
        for (int ks = 0; ks < 4; ks++) {
            const uint32_t b0 = lds32(xb + ks * 32), b1 = lds32(xb + ks * 32 + 16);
            mma(c[(ks & 1) * 2], a[ks * 2], b0, b1);
            mma(c[(ks & 1) * 2 + 1], a[ks * 2 + 1], b0, b1);
        }
        const uint32_t rb = sb + SM_RED + (ew * 288 + t * 72 + g) * 4;
#pragma unroll
        for (int mt = 0; mt < 2; mt++) {
            sts32f(rb + mt * 64, c[mt][0] + c[2 + mt][0]);
            sts32f(rb + mt * 64 + 144, c[mt][1] + c[2 + mt][1]);
            sts32f(rb + mt * 64 + 32, c[mt][2] + c[2 + mt][2]);
            sts32f(rb + mt * 64 + 176, c[mt][3] + c[2 + mt][3]);
        }
    }
    bar_sync(2, 256);
    float2 acc = make_float2(0.f, 0.f);
    if (et < 128) {
        const uint32_t rb = sb + SM_RED + ((et >> 4) * 36 + (et & 15) * 2) * 4;
#pragma unroll
        for (int w = 0; w < 7; w++) {
            const float2 v = lds64f(rb + w * 1152);
            acc.x += v.x;
            acc.y += v.y;
        }
    }
    return acc;
}

struct Params {
    const __nv_bfloat16 *x, *k, *v, *wq, *wo, *w1, *b1, *w2, *b2;
    __nv_bfloat16* out;
    Exchange* xch;
    alignas(64) CUtensorMap map_wo, map_w1, map_w2;
};

__global__ void __launch_bounds__(NTHREADS, 1) fused_decode_kernel(const __grid_constant__ Params p) {
    extern __shared__ __align__(1024) unsigned char smem[];
    const uint32_t sb = (uint32_t)__cvta_generic_to_shared(smem);
    const int tid = threadIdx.x, warp = tid >> 5, lane = tid & 31;
    const int c = blockIdx.x;
    const char* kbase = (const char*)p.k + (size_t)c * (SK * DH * 2);
    const char* vbase = (const char*)p.v + (size_t)c * (SK * DH * 2);

    const int rot = (c * ROT) & (NCH - 1);
    Exchange* const gx = p.xch;
    const bool is_f1 = !(c & 1);
    const int fi = c >> 1;

    if (tid == 128) l2_prefetch(p.wq + c * 14336, 28672, 1);
    if (warp == 4) {
        if (lane == 0) {
#pragma unroll
            for (int s = 0; s < NS; s++) {
                mbar_init(sb + BAR_FULL + 8 * s, 1);
                mbar_init(sb + BAR_EMPTY + 8 * s, 4);
            }
#pragma unroll
            for (int w = 0; w < 8; w++) {
                if (w < 4) mbar_init(sb + BAR_WO + 8 * w, 1);
                mbar_init(sb + BAR_W1 + 8 * w, 1);
            }
            mbar_init(sb + BAR_DRY, 4);
            mbar_init(sb + BAR_WQ, 128);
            mbar_init(sb + BAR_Q, 1);
            mbar_init(sb + BAR_E1, 1);
            mbar_init(sb + BAR_X, 1);
            mbar_init(sb + BAR_X + 8, 1);
            ctl_store(sb + SM_PROG, 0);
            ctl_store(sb + SM_DEPTH, 2);
            asm volatile("fence.mbarrier_init.release.cluster;" ::: "memory");
        }
        __syncthreads();
        if (lane == 0) {
            uint64_t pol;
            asm volatile("createpolicy.fractional.L2::evict_first.b64 %0, 1.0;" : "=l"(pol));
            mbar_expect_tx(sb + BAR_FULL, CHUNK);
            bulk_load(sb + SM_RING, kbase + rot * CHUNK, CHUNK, sb + BAR_FULL, pol);
            spin_or(K1_DELAY, sb + BAR_WQ);
            int s = 1, sl = 0, landed = 0;
            uint32_t ph = 1, phl = 0;
#pragma unroll 1
            for (int i = 1; i <= 2 * NCH; i++) {
                const char* src = (i < NCH ? kbase : vbase) + ((i + rot) & (NCH - 1)) * CHUNK;
                for (int it = 0; landed < (i < 2 * NCH ? i + 1 - (int)ctl_load(sb + SM_DEPTH) : i); it++) {
                    if (mbar_test(sb + BAR_FULL + 8 * sl, phl) || it >= 4 * SPIN_LIMIT) {
                        asm volatile("red.relaxed.gpu.global.add.u32 [%0], 1;" ::"l"(gx->count + 32) : "memory");
                        ctl_store(sb + SM_PROG, ++landed);
                        if (++sl == NS) { sl = 0; phl ^= 1; }
                    } else {
                        __nanosleep(20);
                    }
                }
                if (i == 2 * NCH) break;
                mbar_wait(sb + BAR_EMPTY + 8 * s, ph);
                mbar_expect_tx(sb + BAR_FULL + 8 * s, CHUNK);
                bulk_load(sb + SM_RING + s * CHUNK, src, CHUNK, sb + BAR_FULL + 8 * s, pol);
                if (++s == NS) { s = 0; ph ^= 1; }
            }
        }
    } else if (warp < 4) {
        const int g = lane >> 2, t = lane & 3, r = lane & 7, mi = lane >> 3;
        {
            uint32_t* slot = gx->q + c * 128 + tid;
            uint32_t w = 0;
            xld32(w, slot, 0);
            const int row = tid >> 2, ch = tid & 3;
            const uint32_t dst = sb + SM_WQ + row * 64 + ((ch ^ ((row >> 1) & 3)) << 4);
            const __nv_bfloat16* src = p.wq + row * (NH * DH) + c * 32 + ch * 8;
#pragma unroll
            for (int i = 0; i < 14; i++)
                asm volatile("cp.async.cg.shared.global [%0], [%1], 16;" ::"r"(dst + i * 2048), "l"(src + i * 32 * (NH * DH)) : "memory");
            __syncthreads();
            asm volatile("cp.async.mbarrier.arrive.noinc.shared::cta.b64 [%0];" ::"r"(sb + BAR_WQ) : "memory");
            bar_sync(3, 256);
            w = poll32(slot, w, 0);
            xst32(slot, 0);
            sts32(sb + SM_Q + tid * 4, ~w);
        }
        bar_sync(1, 128);
        asm volatile("fence.proxy.async.shared::cta;" ::: "memory");
        if (tid == 0) mbar_arrive(sb + BAR_Q);
        int s = 0;
        uint32_t ph = 0;
        float rmax = -INFINITY;
        {
            uint32_t qf[32];
#pragma unroll
            for (int i = 0; i < 32; i++) qf[i] = lds32(sb + SM_Q + ((i ^ g) * 4 + t) * 4);
            uint32_t off[4];
#pragma unroll
            for (int i = 0; i < 4; i++)
                off[i] = sb + SM_RING + (warp * 16 + (mi & 1) * 8 + r) * 512 + (((2 * i + (mi >> 1)) ^ r) << 4);
            const bool owner = t == (g >> 1);
            uint32_t pdst = sb + SM_P + (t * 16 + warp * 4 + (g & 1)) * 2;
#pragma unroll 1
            for (int i = 0; i < NCH; i++) {
                mbar_wait(sb + BAR_FULL + 8 * s, ph);
                float acc[4][4] = {};
#pragma unroll
                for (int ks = 0; ks < 16; ks++) {
                    uint32_t a[4];
                    ldsm4(a, off[ks & 3] + s * CHUNK + (ks >> 2) * 128);
                    mma(acc[ks & 3], a, qf[2 * ks], qf[2 * ks + 1]);
                }
                __syncwarp();
                if (lane == 0) mbar_arrive(sb + BAR_EMPTY + 8 * s);
                float v[4];
#pragma unroll
                for (int e = 0; e < 4; e++) v[e] = (acc[0][e] + acc[1][e]) + (acc[2][e] + acc[3][e]);
                const float lo = (g & 1) ? v[1] : v[0], hi = (g & 1) ? v[3] : v[2];
                const uint32_t sc = pack_bf(bf_round(lo) * 0.0625f, bf_round(hi) * 0.0625f);
                if (owner) {
                    sts16(pdst, sc & 0xffffu);
                    sts16(pdst + 4, sc >> 16);
                    rmax = fmaxf(rmax, fmaxf(bf_lo(sc), bf_hi(sc)));
                }
                pdst += 128;
                if (++s == NS) { s = 0; ph ^= 1; }
            }
        }
        {
#pragma unroll
            for (int o = 16; o; o >>= 1) rmax = fmaxf(rmax, __shfl_xor_sync(0xffffffffu, rmax, o));
            if (lane == 0) sts32f(sb + SM_STAT + warp * 4, rmax);
            bar_sync(1, 128);
            const uint4 mx = lds128(sb + SM_STAT);
            const float m = fmaxf(fmaxf(__uint_as_float(mx.x), __uint_as_float(mx.y)),
                                  fmaxf(__uint_as_float(mx.z), __uint_as_float(mx.w)));
            float e[32];
            float sum = 0.f;
#pragma unroll
            for (int i = 0; i < 4; i++) {
                const uint4 w = lds128(sb + SM_P + (i * 128 + tid) * 16);
                const uint32_t ww[4] = {w.x, w.y, w.z, w.w};
#pragma unroll
                for (int j = 0; j < 4; j++) {
                    e[i * 8 + 2 * j] = __expf(bf_lo(ww[j]) - m);
                    e[i * 8 + 2 * j + 1] = __expf(bf_hi(ww[j]) - m);
                    sum += e[i * 8 + 2 * j] + e[i * 8 + 2 * j + 1];
                }
            }
#pragma unroll
            for (int o = 16; o; o >>= 1) sum += __shfl_xor_sync(0xffffffffu, sum, o);
            if (lane == 0) sts32f(sb + SM_STAT + 16 + warp * 4, sum);
            bar_sync(1, 128);
            const uint4 sm = lds128(sb + SM_STAT + 16);
            const float inv = 1.f / ((__uint_as_float(sm.x) + __uint_as_float(sm.y)) +
                                     (__uint_as_float(sm.z) + __uint_as_float(sm.w)));
#pragma unroll
            for (int i = 0; i < 4; i++) {
                uint4 w;
                w.x = pack_bf(e[i * 8 + 0] * inv, e[i * 8 + 1] * inv);
                w.y = pack_bf(e[i * 8 + 2] * inv, e[i * 8 + 3] * inv);
                w.z = pack_bf(e[i * 8 + 4] * inv, e[i * 8 + 5] * inv);
                w.w = pack_bf(e[i * 8 + 6] * inv, e[i * 8 + 7] * inv);
                sts128(sb + SM_P + (i * 128 + tid) * 16, w);
            }
            bar_sync(1, 128);
        }
        {
            uint32_t off[4];
#pragma unroll
            for (int i = 0; i < 4; i++)
                off[i] = sb + SM_RING + ((mi >> 1) * 8 + r) * 512 + warp * 128 + (((2 * i + (mi & 1)) ^ r) << 4);
            const uint32_t pmask = t == (g >> 1) ? ((g & 1) ? 0xffff0000u : 0x0000ffffu) : 0u;
            uint32_t* odst = gx->o + ((c & 15) * 8 + (c >> 4)) * 128 + (warp * 2 + (t >> 1)) * 16 + (g >> 1) * 4 +
                             (t & 1) * 2 + (g & 1);
            uint32_t lane2;
            asm volatile("mov.u32 %0, %%laneid;" : "=r"(lane2));
#pragma unroll 1
            for (int pass = 0; pass < 2; pass++) {
                int n = pass * NCH;
                asm volatile("" : "+r"(n));
                float acc[4][4] = {};
                uint32_t psrc = sb + SM_P + t * 32;
                uint32_t va[8][4], vb[8][4] = {};
                uint32_t pt[4] = {};
                uint32_t cur[4];
#pragma unroll
                for (int j = 0; j < 4; j++) cur[j] = off[j] + s * CHUNK;
                uint32_t bar = sb + BAR_FULL + 8 * s, ready = 0;
#pragma unroll 1
                for (int i = n; i > 0; i--) {
                    if (!ready) mbar_wait(bar, ph);
                    const bool wrap = bar == sb + BAR_FULL + 8 * (NS - 1);
                    const uint32_t barn = wrap ? sb + BAR_FULL : bar + 8;
                    ph ^= wrap;
                    const uint4 p0 = lds128(psrc), p1 = lds128(psrc + 16);
#pragma unroll
                    for (int j = 0; j < 2; j++) ldsm4t(va[j], cur[j & 3] + (j >> 2) * 8192);
                    uint32_t tok;
                    asm volatile("{\n.reg .pred p;\nmbarrier.test_wait.parity.shared::cta.b64 p, [%2], %3;\n"
                                 "selp.u32 %0, 1, 0, p;\nselp.u32 %1, %4, %5, p;\n}"
                                 : "=r"(ready), "=r"(tok) : "r"(barn), "r"(ph), "r"(lane), "r"(lane2) : "memory");
#pragma unroll
                    for (int j = 2; j < 8; j++) ldsm4t(va[j], cur[j & 3] + (j >> 2) * 8192);
#pragma unroll
                    for (int j = 0; j < 8; j++) mma(acc[j & 3], vb[j], pt[(j >> 2) * 2], pt[(j >> 2) * 2 + 1]);
#pragma unroll
                    for (int j = 0; j < 8; j++) ldsm4t(vb[j], cur[j & 3] + (2 + (j >> 2)) * 8192);
                    asm volatile("{\n.reg .pred p;\nsetp.eq.u32 p, %1, 0;\n@p mbarrier.arrive.shared::cta.b64 _, [%0];\n}"
                                 ::"r"(bar + 8 * NS), "r"(tok) : "memory");
                    mma(acc[0], va[0], p0.x & pmask, p0.y & pmask);
                    mma(acc[1], va[1], p0.x & pmask, p0.y & pmask);
                    mma(acc[2], va[2], p0.x & pmask, p0.y & pmask);
                    mma(acc[3], va[3], p0.x & pmask, p0.y & pmask);
                    mma(acc[0], va[4], p0.z & pmask, p0.w & pmask);
                    mma(acc[1], va[5], p0.z & pmask, p0.w & pmask);
                    mma(acc[2], va[6], p0.z & pmask, p0.w & pmask);
                    mma(acc[3], va[7], p0.z & pmask, p0.w & pmask);
                    pt[0] = p1.x & pmask;
                    pt[1] = p1.y & pmask;
                    pt[2] = p1.z & pmask;
                    pt[3] = p1.w & pmask;
                    psrc += 128;
                    bar = barn;
                    const uint32_t step = wrap ? -(NS - 1) * CHUNK : CHUNK;
#pragma unroll
                    for (int j = 0; j < 4; j++) cur[j] += step;
                }
#pragma unroll
                for (int j = 0; j < 8; j++) mma(acc[j & 3], vb[j], pt[(j >> 2) * 2], pt[(j >> 2) * 2 + 1]);
                float ev[4], od[4];
#pragma unroll
                for (int T = 0; T < 4; T++) {
                    ev[T] = acc[T][0] + acc[T][3];
                    od[T] = acc[T][1] + acc[T][2];
                }
                ev[0] += __shfl_xor_sync(0xffffffffu, ev[1], 1);
                od[0] += __shfl_xor_sync(0xffffffffu, od[1], 1);
                ev[2] += __shfl_xor_sync(0xffffffffu, ev[3], 1);
                od[2] += __shfl_xor_sync(0xffffffffu, od[3], 1);
                ev[0] += __shfl_xor_sync(0xffffffffu, ev[2], 2);
                od[0] += __shfl_xor_sync(0xffffffffu, od[2], 2);
                const float other = __shfl_xor_sync(0xffffffffu, (g & 1) ? ev[0] : od[0], 4);
                const uint32_t w = (g & 1) ? pack_bf(other, od[0]) : pack_bf(ev[0], other);
                xst32(odst, n ? w : EMPTY);
                __syncwarp();
                if (!n && lane == 0) mbar_arrive(sb + BAR_DRY);
                if (c < 112) {
                    bar_sync(1, 128);
                    if (tid == 0) {
                        const uint32_t on = n ? 0xffffffffu : 0u;
                        mbar_wait(sb + BAR_W0, ~on & 1);
                        l2_prefetch(p.w1 + c * 7168, 14336, on);
                        spin((is_f1 ? W1_DELAY : PF_DELAY) & on);
                        if (!is_f1) {
                            l2_prefetch(p.w2 + fi * 14336, 28672, on);
                            mbar_wait(sb + BAR_E1, ~on & 1);
                            spin(W2_DELAY & on);
                        }
                        tile_loads(sb + (n ? SM_WX : SM_WO + 8192), is_f1 ? &p.map_w1 : &p.map_w2,
                                   is_f1 ? fi * 32 : (fi % 28) * 16, n ? 0 : 1 << 20, is_f1 ? 64 : 224, is_f1 ? 4096 : 7168,
                                   sb + (n ? BAR_W1 : BAR_X), n ? 8 - is_f1 : 1);
                    }
                }
            }
        }
    } else {
        const int ew = warp - 5, et = tid - 160;
        const int r = lane & 7, mi = lane >> 3;
        {
            uint32_t w[7];
#pragma unroll
            for (int i = 0; i < 7; i++)
                asm volatile("ld.global.nc.u32 %0, [%1];" : "=r"(w[i]) : "l"((const uint32_t*)p.x + ew * 224 + i * 32 + lane));
            __syncthreads();
            layernorm_row(w, sb + SM_XN + ew * 912, lane);
            mbar_wait(sb + BAR_WQ, 0);
            uint32_t a[8][4];
            frags_w448(a, sb + SM_WQ, ew, lane);
            const float2 q = gemv448(a, sb, ew, lane, et);
            if (et < 128) {
                xst32(gx->q + ((et >> 4) * 16 + (c >> 3)) * 128 + (c & 7) * 16 + (et & 15), ~pack_bf(q.x, q.y));
                asm volatile("bar.arrive 3, 256;" ::: "memory");
            }
        }
        const int hh = c / 7, jj = c - hh * 7;
        const int cg = fi % 28, half = fi / 28;
        const int ht0 = (c - 112) * 7 + min(ew, 6);
        uint32_t side;
        asm volatile("ld.global.nc.u32 %0, [%1];" : "=r"(side)
                     : "l"(c < 112 ? (is_f1 ? p.b1 + fi * 32 + (et & 15) * 2 : p.b2 + cg * 16 + r * 2)
                           : p.x + ((ht0 & 6) + (mi & 1)) * DM + (ht0 >> 3) * 32 + (r & 3) * 8 + (ht0 & 1) * 4 + (r >> 2) * 2));
        uint32_t seen_prog = 0;
#pragma unroll 1
        for (int pass = 0; pass < 2; pass++) {
            uint32_t live = pass;
            asm volatile("" : "+r"(live));
            const uint32_t want = 0u - live, wipe = ~want;
            const int et = pin(tid - 160), ew = et >> 5, lane = et & 31;
            const int g = lane >> 2, t = lane & 3, r = lane & 7, mi = lane >> 3;
            if (et == 0) {
                if (!live) mbar_wait(sb + BAR_Q, 0);
#pragma unroll 1
                for (int it = 0; it < SPIN_LIMIT; it++) {
                    const uint32_t prog = ctl_load(sb + SM_PROG);
                    int total = 0;
                    if (prog == seen_prog) __nanosleep(100);
                    if (prog != seen_prog || prog >= 2 * NCH - 8)
                        asm volatile("ld.relaxed.gpu.global.u32 %0, [%1];" : "=r"(total) : "l"(gx->count + 32) : "memory");
                    if (total >= ALL_CHUNKS - LIFT_LEFT) {
                        ctl_store(sb + SM_DEPTH, NS);
                    } else if (prog != seen_prog) {
                        const int lead = prog * NCTA - total;
                        ctl_store(sb + SM_DEPTH, lead >= LEAD1 ? 1 : lead >= LEAD2 ? 2 : lead >= LEAD2 - 128 ? 3 : lead >= LEAD2 - 256 ? 4 : NS);
                    }
                    seen_prog = prog;
                    if (live ? total >= ALL_CHUNKS - TRIG_LEFT : mbar_test(sb + BAR_DRY, 0)) break;
                }
                tile_loads(sb + SM_WO, &p.map_wo, jj * 64, live ? hh * 256 : 1 << 20, 64, 8192, sb + (live ? BAR_WO : BAR_X + 8),
                           c >= 112 ? 0 : live ? 4 : 1);
            } else if (et == 32 && live) {
                uint32_t seen;
                mbar_wait(sb + BAR_DRY, 0);
                asm volatile("atom.release.gpu.global.add.u32 %0, [%1], 1;" : "=r"(seen) : "l"(gx->count) : "memory");
                int it = 0;
                for (seen++; seen < NCTA && ++it < SPIN_LIMIT;) {
                    __nanosleep(512);
                    asm volatile("ld.relaxed.gpu.global.u32 %0, [%1];" : "=r"(seen) : "l"(gx->count) : "memory");
                }
                asm volatile("ld.acquire.gpu.global.u32 %0, [%1];" : "=r"(seen) : "l"(gx->count) : "memory");
            }
            __syncwarp();
            bar_sync(2, 256);
            if (c >= 112) {
                if (ew < 7) {
                    const bool odd = mi & 1;
                    const int ht = (c - 112) * 7 + ew;
                    float a0, a1;
                    uint32_t* const dst = gx->h + pin((((mi >> 1) * 14 + (ht >> 3)) * 8 + (ht & 6) + (mi & 1)) * 16 + (ht & 1) * 8 + r);
                    Poll<4, 128> in(gx->part + pin(ht * 512 + lane * 4), want, want);
                    in.finish([&] {
                        const uint4 (&v)[4] = in.v;
                        const float f0 = (__uint_as_float(v[0].x) + __uint_as_float(v[1].x)) + (__uint_as_float(v[2].x) + __uint_as_float(v[3].x));
                        const float f1 = (__uint_as_float(v[0].y) + __uint_as_float(v[1].y)) + (__uint_as_float(v[2].y) + __uint_as_float(v[3].y));
                        const float f2 = (__uint_as_float(v[0].z) + __uint_as_float(v[1].z)) + (__uint_as_float(v[2].z) + __uint_as_float(v[3].z));
                        const float f3 = (__uint_as_float(v[0].w) + __uint_as_float(v[1].w)) + (__uint_as_float(v[2].w) + __uint_as_float(v[3].w));
                        a0 = (odd ? f1 : f0) + __shfl_xor_sync(0xffffffffu, odd ? f0 : f1, 8);
                        a1 = (odd ? f3 : f2) + __shfl_xor_sync(0xffffffffu, odd ? f2 : f3, 8);
                    });
                    a0 += __shfl_xor_sync(0xffffffffu, a0, 16);
                    a1 += __shfl_xor_sync(0xffffffffu, a1, 16);
                    xst32(dst, bf2_add(side, pack_bf(a0, a1)) | wipe);
                }
                if (!live) bar_sync(5, 256);
                continue;
            }
            {
                const uint32_t fa = pin(sb + SM_WO + ((ew >> 1) * 64 + (mi >> 1) * 8 + r) * 128 + ((((ew & 1) * 4 + (mi & 1)) ^ r) << 4));
                const uint32_t wb = pin(sb + SM_RED + ((ew >> 1) * 544 + t * 136 + (ew & 1) * 64 + g * 2) * 4);
                const uint32_t rb = pin(sb + SM_RED + ((ew & 3) * 136 + ((ew >> 2) * 32 + (r >> 1) * 8 + mi * 2 + (r & 1)) * 2) * 4);
                uint32_t* const pdst = gx->part + pin((((jj * 8 + ew) * 2 + (lane >> 4)) * 16 + hh) * 32 + (lane & 15) * 2);
                Poll<2, 16> in(gx->o + pin((hh * 8 + g) * 128 + (ew >> 1) * 32 + t * 4), want, want);
                in.until(sb + BAR_WO + 8 * (ew >> 1));
                uint32_t a[8][4];
#pragma unroll
                for (int i = 0; i < 4; i++) {
                    const int ks = (i >> 1) + (i & 1) * 2;
                    ldsm4t(a[ks * 2], fa + ks * 2048);
                    ldsm4t(a[ks * 2 + 1], (fa ^ 32) + ks * 2048);
                }
                float acc[2][2][4];
                in.finish([&] {
#pragma unroll
                    for (int i = 0; i < 2; i++) {
                        mma0(acc[i][0], a[i * 4], in.v[i].x, in.v[i].y);
                        mma0(acc[i][1], a[i * 4 + 1], in.v[i].x, in.v[i].y);
                    }
#pragma unroll
                    for (int mt = 0; mt < 2; mt++) {
                        mma(acc[0][mt], a[2 + mt], in.v[0].z, in.v[0].w);
                        mma(acc[1][mt], a[6 + mt], in.v[1].z, in.v[1].w);
                    }
                });
#pragma unroll
                for (int mt = 0; mt < 2; mt++) {
                    sts64f(wb + mt * 128, acc[0][mt][0] + acc[1][mt][0], acc[0][mt][1] + acc[1][mt][1]);
                    sts64f(wb + mt * 128 + 64, acc[0][mt][2] + acc[1][mt][2], acc[0][mt][3] + acc[1][mt][3]);
                }
                bar_sync(2, 256);
                float2 v[4];
#pragma unroll
                for (int w = 0; w < 4; w++) v[w] = lds64f(rb + w * 2176);
                const float s0 = (v[0].x + v[1].x) + (v[2].x + v[3].x);
                const float s1 = (v[0].y + v[1].y) + (v[2].y + v[3].y);
                xst64(pdst, __float_as_uint(s0) | wipe, __float_as_uint(s1) | wipe);
            }
            if (et == 0 && live) mbar_arrive(sb + BAR_E1);
            const uint32_t wbar = sb + BAR_W1 + 8 * ew;
            if (is_f1) {
                constexpr uint32_t ONES = 0x3f803f80u;
                if (ew < 7) {
                    const int b = (et >> 4) & 7, pr = et & 15;
                    const uint32_t fa = pin(sb + SM_WX + (ew * 64 + (mi >> 1) * 8 + r) * 64 + (((mi & 1) ^ (r >> 1)) << 4));
                    const uint32_t wb = pin(sb + SM_RED + (ew * 288 + t * 72 + g) * 4);
                    const uint32_t sw = pin(sb + SM_RED + (ew * 288 + g * 36 + (t == (g >> 1) ? 32 : 34)) * 4);
                    const uint32_t rs = pin(sb + SM_RED + b * 144 + 128), rz = pin(sb + SM_RED + b * 144 + pr * 8);
                    const uint32_t cw = pin(sb + SM_XN + (ew * 32 + g + (t >> 1) * 16 + (t & 1) * 8) * 4), cr = pin(sb + SM_XN + pr * 8);
                    const bool odd = pin(g & 1);
                    uint32_t* const dst = gx->r + pin((((b >> 2) * 56 + fi) * 4 + (b & 3)) * 16 + (pr & 3) * 4 + (pr >> 2));
                    Poll<2, 128> in(gx->h + pin(((fi & 1) * 14 + ew * 2) * 128 + lane * 4), want, want);
                    mbar_wait(wbar, wipe & 1);
                    uint32_t a[8][4];
#pragma unroll
                    for (int ks = 0; ks < 4; ks++) {
                        ldsm4t(a[ks * 2], fa + ks * 1024);
                        ldsm4t(a[ks * 2 + 1], (fa ^ 32) + ks * 1024);
                    }
                    float cs[2][4] = {}, z[2][2][4], st[2][4];
#pragma unroll
                    for (int ks = 0; ks < 4; ks++) {
                        mma(cs[0], a[ks * 2], ONES, ONES);
                        mma(cs[1], a[ks * 2 + 1], ONES, ONES);
                    }
                    sts32f(cw, (t & 1) ? ((t & 2) ? cs[1][2] : cs[0][2]) : ((t & 2) ? cs[1][0] : cs[0][0]));
                    bar_sync(4, 224);
                    float2 cv[7];
#pragma unroll
                    for (int w = 0; w < 7; w++) cv[w] = lds64f(cr + w * 128);
                    const float cs0 = ((cv[0].x + cv[1].x) + (cv[2].x + cv[3].x)) + ((cv[4].x + cv[5].x) + cv[6].x);
                    const float cs1 = ((cv[0].y + cv[1].y) + (cv[2].y + cv[3].y)) + ((cv[4].y + cv[5].y) + cv[6].y);
                    in.finish([&] {
#pragma unroll
                        for (int i = 0; i < 2; i++) {
                            const uint32_t sa[4] = {in.v[i].x, ONES, in.v[i].y, ONES};
                            mma0(z[i][0], a[i * 4], in.v[i].x, in.v[i].y);
                            mma0(z[i][1], a[i * 4 + 1], in.v[i].x, in.v[i].y);
                            mma0(st[i], sa, in.v[i].x, in.v[i].y);
                        }
                    });
#pragma unroll
                    for (int i = 0; i < 2; i++) mma(z[i][0], a[i * 4 + 2], in.v[i].z, in.v[i].w);
#pragma unroll
                    for (int i = 0; i < 2; i++) mma(z[i][1], a[i * 4 + 3], in.v[i].z, in.v[i].w);
#pragma unroll
                    for (int i = 0; i < 2; i++) {
                        const uint32_t sa[4] = {in.v[i].z, ONES, in.v[i].w, ONES};
                        mma(st[i], sa, in.v[i].z, in.v[i].w);
                    }
#pragma unroll
                    for (int mt = 0; mt < 2; mt++) {
                        sts32f(wb + mt * 64, z[0][mt][0] + z[1][mt][0]);
                        sts32f(wb + mt * 64 + 144, z[0][mt][1] + z[1][mt][1]);
                        sts32f(wb + mt * 64 + 32, z[0][mt][2] + z[1][mt][2]);
                        sts32f(wb + mt * 64 + 176, z[0][mt][3] + z[1][mt][3]);
                    }
                    sts64f(sw, odd ? st[0][3] + st[1][3] : st[0][2] + st[1][2], odd ? st[0][1] + st[1][1] : st[0][0] + st[1][0]);
                    bar_sync(4, 224);
                    if (ew < 4) {
                        float2 sv[7], zv[7];
#pragma unroll
                        for (int w = 0; w < 7; w++) sv[w] = lds64f(rs + w * 1152);
#pragma unroll
                        for (int w = 0; w < 7; w++) zv[w] = lds64f(rz + w * 1152);
                        const float mu = (((sv[0].x + sv[1].x) + (sv[2].x + sv[3].x)) + ((sv[4].x + sv[5].x) + sv[6].x)) * (1.f / DM);
                        const float sq = ((sv[0].y + sv[1].y) + (sv[2].y + sv[3].y)) + ((sv[4].y + sv[5].y) + sv[6].y);
                        const float inv = inv_std(bf_round(fmaxf(fmaf(sq, 1.f / DM, -mu * mu), 0.f)));
                        const float mean = bf_round(mu);
                        const float z0 = ((zv[0].x + zv[1].x) + (zv[2].x + zv[3].x)) + ((zv[4].x + zv[5].x) + zv[6].x);
                        const float z1 = ((zv[0].y + zv[1].y) + (zv[2].y + zv[3].y)) + ((zv[4].y + zv[5].y) + zv[6].y);
                        const uint32_t u = pack_bf(fmaf(-mean, cs0, z0) * inv, fmaf(-mean, cs1, z1) * inv);
                        xst32(dst, bf2_relu_sq(bf2_add(u, side)) | wipe);
                    }
                }
            } else {
                const uint32_t fa = pin(sb + SM_WX + (ew * 224 + (mi >> 1) * 8 + r) * 32 + (((mi & 1) ^ (r >> 2)) << 4));
                const uint32_t wb = pin(sb + SM_XN + (ew * 160 + (t & 1) * 80 + (g >> 1) * 4 + (t >> 1) * 2 + (g & 1)) * 4);
                const uint32_t rb = pin(sb + SM_XN + (mi * 40 + r * 4) * 4);
                const bool upper = pin(t >> 1), first = pin(ew == 0);
                uint32_t* const dst = (live ? (uint32_t*)p.out : gx->sink) + pin((half * 4 + mi) * 224 + cg * 8 + r);
                Poll<4, 128, true> in(gx->r + pin((half * 56 + ew * 7) * 64 + lane * 4), want, lane < 16 ? want : 0u,
                                      gx->h + pin((((fi & 1) * 14 + (cg >> 1)) * 8 + half * 4 + mi) * 16 + (r & 3) * 4 +
                                                  (cg & 1) * 2 + (r >> 2)),
                                      ew == 0 ? want : 0u);
                mbar_wait(wbar, wipe & 1);
                uint32_t a[14][4];
#pragma unroll
                for (int ks = 0; ks < 14; ks++) ldsm4t(a[ks], fa + ks * 512);
                float acc[4][4];
                const auto step = [&](int i) {
                    mma(acc[0], a[4 * i], in.v[i].x, in.v[i].y);
                    mma(acc[1], a[4 * i + 1], in.v[i].z, in.v[i].w);
                    if (i < 3) {
                        mma(acc[2], a[4 * i + 2], in.v[i].x, in.v[i].y);
                        mma(acc[3], a[4 * i + 3], in.v[i].z, in.v[i].w);
                    }
                };
                in.finish([&] {
                    mma0(acc[0], a[0], in.v[0].x, in.v[0].y);
                    mma0(acc[1], a[1], in.v[0].z, in.v[0].w);
                    mma0(acc[2], a[2], in.v[0].x, in.v[0].y);
                    mma0(acc[3], a[3], in.v[0].z, in.v[0].w);
                    step(1);
                });
                step(2);
                step(3);
                sts32f(wb, upper ? acc[2][0] + acc[3][0] : acc[0][0] + acc[1][0]);
                sts32f(wb + 160, upper ? acc[2][1] + acc[3][1] : acc[0][1] + acc[1][1]);
                sts32f(wb + 64, upper ? acc[2][2] + acc[3][2] : acc[0][2] + acc[1][2]);
                sts32f(wb + 224, upper ? acc[2][3] + acc[3][3] : acc[0][3] + acc[1][3]);
                bar_sync(2, 256);
                if (first) {
                    float x[8], y[8];
#pragma unroll
                    for (int w = 0; w < 8; w++) {
                        const uint4 q = lds128(rb + w * 640);
                        x[w] = __uint_as_float(q.x) + __uint_as_float(q.z);
                        y[w] = __uint_as_float(q.y) + __uint_as_float(q.w);
                    }
                    const float s0 = ((x[0] + x[1]) + (x[2] + x[3])) + ((x[4] + x[5]) + (x[6] + x[7]));
                    const float s1 = ((y[0] + y[1]) + (y[2] + y[3])) + ((y[4] + y[5]) + (y[6] + y[7]));
                    *dst = bf2_add(in.word, bf2_add(pack_bf(s0, s1), side));
                    asm volatile("{\n.reg .pred p;\nsetp.ne.u32 p, %0, 0;\n@p exit;\n}" ::"r"(live) : "memory");
                } else if (fi == 0 && et == 32 && live) {
                    xst32(gx->count, 0);
                    xst32(gx->count + 32, 0);
                }
            }
            if (!live) bar_sync(5, 256);
        }
    }
}

using EncodeFn = CUresult (*)(CUtensorMap*, CUtensorMapDataType, cuuint32_t, void*, const cuuint64_t*, const cuuint64_t*,
                              const cuuint32_t*, const cuuint32_t*, CUtensorMapInterleave, CUtensorMapSwizzle,
                              CUtensorMapL2promotion, CUtensorMapFloatOOBfill);

void encode_map(EncodeFn fn, CUtensorMap* map, const void* base, int rows, int cols, int box_rows, int box_cols,
                CUtensorMapSwizzle swizzle) {
    const cuuint64_t dims[2] = {(cuuint64_t)cols, (cuuint64_t)rows};
    const cuuint64_t strides[1] = {(cuuint64_t)cols * 2};
    const cuuint32_t box[2] = {(cuuint32_t)box_cols, (cuuint32_t)box_rows};
    const cuuint32_t steps[2] = {1, 1};
    fn(map, CU_TENSOR_MAP_DATA_TYPE_BFLOAT16, 2, const_cast<void*>(base), dims, strides, box, steps,
       CU_TENSOR_MAP_INTERLEAVE_NONE, swizzle, CU_TENSOR_MAP_L2_PROMOTION_L2_128B, CU_TENSOR_MAP_FLOAT_OOB_FILL_NONE);
}

}

extern "C" void kernel_launch(void* const* d_in, const int* in_sizes, int n_in, void* d_out, int out_size) {
    (void)in_sizes; (void)n_in; (void)out_size;
    Params p;
    p.x = (const __nv_bfloat16*)d_in[0];
    p.k = (const __nv_bfloat16*)d_in[1];
    p.v = (const __nv_bfloat16*)d_in[2];
    p.wq = (const __nv_bfloat16*)d_in[3];
    p.wo = (const __nv_bfloat16*)d_in[4];
    p.w1 = (const __nv_bfloat16*)d_in[6];
    p.b1 = (const __nv_bfloat16*)d_in[7];
    p.w2 = (const __nv_bfloat16*)d_in[8];
    p.b2 = (const __nv_bfloat16*)d_in[9];
    p.out = (__nv_bfloat16*)d_out;
    cudaGetSymbolAddress((void**)&p.xch, g_x);
    void* fn = nullptr;
    cudaDriverEntryPointQueryResult found;
    cudaGetDriverEntryPoint("cuTensorMapEncodeTiled", &fn, cudaEnableDefault, &found);
    encode_map((EncodeFn)fn, &p.map_wo, p.wo, NH * DH, DM, 64, 64, CU_TENSOR_MAP_SWIZZLE_128B);
    encode_map((EncodeFn)fn, &p.map_w1, p.w1, DM, FF, 64, 32, CU_TENSOR_MAP_SWIZZLE_64B);
    encode_map((EncodeFn)fn, &p.map_w2, p.w2, FF, DM, 224, 16, CU_TENSOR_MAP_SWIZZLE_32B);
    cudaFuncSetAttribute(fused_decode_kernel, cudaFuncAttributeMaxDynamicSharedMemorySize, SM_TOTAL);
    fused_decode_kernel<<<NCTA, NTHREADS, SM_TOTAL>>>(p);
}
```

```cpp
#include <cuda.h>
#include <cuda_runtime.h>
#include <cuda_bf16.h>
#include <stdint.h>

namespace {

constexpr int DM = 448, NH = 16, SK = 4096, DH = 256, FF = 1792;
constexpr int NCTA = 128;
constexpr int CHUNK = 32768;
constexpr int NCH = SK / 64;
constexpr int NS = 5;
constexpr int ALL_CHUNKS = NCTA * 2 * NCH;
constexpr int LEAD1 = 128;
constexpr int LEAD2 = -128;
constexpr int LIFT_LEFT = 370;
constexpr int TRIG_LEFT = 220;
constexpr int K1_DELAY = 2000;
constexpr int W1_DELAY = 600;
constexpr int PF_DELAY = 500;
constexpr int W2_DELAY = 600;
constexpr int ROT = 32;
constexpr int R_DELAY = 200;
constexpr int O_DELAY = 2000;
constexpr int NTHREADS = 13 * 32;
constexpr int SPIN_LIMIT = 1 << 18;
constexpr int WAIT_LIMIT = 1 << 14;

constexpr int SM_RING = 0;
constexpr int SM_WX = 0;
constexpr int SM_WQ = NS * CHUNK;
constexpr int SM_WO = SM_WQ;
constexpr int SM_P = SM_WQ + 32768;
constexpr int SM_RED = SM_P + 8192;
constexpr int SM_XN = SM_RED + 4 * 544 * 4;
constexpr int SM_Q = SM_XN + 8 * 456 * 2;
constexpr int SM_STAT = SM_Q + 512;
constexpr int SM_PROG = SM_STAT + 32, SM_DEPTH = SM_STAT + 36;
constexpr int SM_BAR = SM_STAT + 64;
constexpr int BAR_FULL = SM_BAR, BAR_EMPTY = BAR_FULL + 8 * NS, BAR_WO = BAR_EMPTY + 8 * NS, BAR_DRY = BAR_WO + 32,
              BAR_WQ = BAR_DRY + 8, BAR_Q = BAR_WQ + 8, BAR_W0 = BAR_WO + 24, BAR_E1 = BAR_Q + 8, BAR_X = BAR_E1 + 8,
              BAR_W1 = BAR_X + 16;
constexpr int SM_TOTAL = BAR_W1 + 64;
static_assert(SM_TOTAL <= 232448, "shared memory budget");

struct Exchange {
    uint32_t q[NCTA * 128];
    uint32_t o[NH * 8 * 128];
    uint32_t part[14 * 8 * 16 * 32];
    uint32_t h[2 * 14 * 8 * 16];
    uint32_t r[2 * 56 * 4 * 16];
    uint32_t count[64];
    uint32_t sink[8 * 224];
};
__device__ __align__(128) Exchange g_x;

__device__ __forceinline__ void mbar_init(uint32_t bar, uint32_t count) {
    asm volatile("mbarrier.init.shared::cta.b64 [%0], %1;" ::"r"(bar), "r"(count) : "memory");
}
__device__ __forceinline__ void mbar_arrive(uint32_t bar) {
    asm volatile("mbarrier.arrive.shared::cta.b64 _, [%0];" ::"r"(bar) : "memory");
}
__device__ __forceinline__ void mbar_expect_tx(uint32_t bar, uint32_t bytes) {
    asm volatile("mbarrier.arrive.expect_tx.shared::cta.b64 _, [%0], %1;" ::"r"(bar), "r"(bytes) : "memory");
}
__device__ __forceinline__ void mbar_wait(uint32_t bar, uint32_t parity) {
    asm volatile("{\n.reg .pred p, q;\n.reg .u32 n;\nmov.u32 n, %2;\n"
                 "RETRY:\nsub.u32 n, n, 1;\nsetp.ne.u32 q, n, 0;\n"
                 "mbarrier.try_wait.parity.shared::cta.b64 p, [%0], %1;\nand.pred q, q, !p;\n@q bra RETRY;\n}"
                 ::"r"(bar), "r"(parity), "n"(WAIT_LIMIT) : "memory");
}
__device__ __forceinline__ uint32_t mbar_test(uint32_t bar, uint32_t parity) {
    uint32_t done;
    asm volatile("{\n.reg .pred p;\nmbarrier.test_wait.parity.shared::cta.b64 p, [%1], %2;\nselp.u32 %0, 1, 0, p;\n}"
                 : "=r"(done) : "r"(bar), "r"(parity) : "memory");
    return done;
}
__device__ __forceinline__ void spin(uint32_t cycles) {
    const uint32_t t0 = (uint32_t)clock();
    do {
    } while ((uint32_t)clock() - t0 < cycles);
}
__device__ __forceinline__ void spin_or(uint32_t cycles, uint32_t bar) {
    const uint32_t t0 = (uint32_t)clock();
    do {
    } while (!mbar_test(bar, 0) && (uint32_t)clock() - t0 < cycles);
}
__device__ __forceinline__ void l2_prefetch(const void* src, uint32_t bytes, uint32_t on) {
    asm volatile("{\n.reg .pred p;\nsetp.ne.u32 p, %2, 0;\n@p cp.async.bulk.prefetch.L2.global [%0], %1;\n}"
                 ::"l"(src), "r"(bytes), "r"(on) : "memory");
}
__device__ __forceinline__ void bulk_load(uint32_t dst, const void* src, uint32_t bytes, uint32_t bar, uint64_t pol) {
    asm volatile("cp.async.bulk.shared::cluster.global.mbarrier::complete_tx::bytes.L2::cache_hint [%0], [%1], %2, [%3], %4;"
                 ::"r"(dst), "l"(src), "r"(bytes), "r"(bar), "l"(pol) : "memory");
}
__device__ __forceinline__ void tile_loads(uint32_t dst, const CUtensorMap* map, int col, int row, int rows, uint32_t bytes,
                                           uint32_t bar, int n) {
#pragma unroll 1
    for (int i = 0; i < n; i++, dst += bytes, row += rows, bar += 8) {
        mbar_expect_tx(bar, bytes);
        asm volatile("cp.async.bulk.tensor.2d.shared::cluster.global.mbarrier::complete_tx::bytes [%0], [%1, {%2, %3}], [%4];"
                     ::"r"(dst), "l"(map), "r"(col), "r"(row), "r"(bar) : "memory");
    }
}
__device__ __forceinline__ void bar_sync(int id, int n) { asm volatile("bar.sync %0, %1;" ::"r"(id), "r"(n) : "memory"); }

__device__ __forceinline__ void ldsm4(uint32_t (&r)[4], uint32_t a) {
    asm volatile("ldmatrix.sync.aligned.m8n8.x4.shared.b16 {%0,%1,%2,%3}, [%4];"
                 : "=r"(r[0]), "=r"(r[1]), "=r"(r[2]), "=r"(r[3]) : "r"(a) : "memory");
}
__device__ __forceinline__ void ldsm4t(uint32_t (&r)[4], uint32_t a) {
    asm volatile("ldmatrix.sync.aligned.m8n8.x4.trans.shared.b16 {%0,%1,%2,%3}, [%4];"
                 : "=r"(r[0]), "=r"(r[1]), "=r"(r[2]), "=r"(r[3]) : "r"(a) : "memory");
}
__device__ __forceinline__ void mma(float (&c)[4], const uint32_t (&a)[4], uint32_t b0, uint32_t b1) {
    asm volatile("mma.sync.aligned.m16n8k16.row.col.f32.bf16.bf16.f32 {%0,%1,%2,%3}, {%4,%5,%6,%7}, {%8,%9}, {%0,%1,%2,%3};"
                 : "+f"(c[0]), "+f"(c[1]), "+f"(c[2]), "+f"(c[3])
                 : "r"(a[0]), "r"(a[1]), "r"(a[2]), "r"(a[3]), "r"(b0), "r"(b1));
}
__device__ __forceinline__ void mma0(float (&c)[4], const uint32_t (&a)[4], uint32_t b0, uint32_t b1) {
    asm volatile("mma.sync.aligned.m16n8k16.row.col.f32.bf16.bf16.f32 {%0,%1,%2,%3}, {%4,%5,%6,%7}, {%8,%9}, {%10,%10,%10,%10};"
                 : "=f"(c[0]), "=f"(c[1]), "=f"(c[2]), "=f"(c[3])
                 : "r"(a[0]), "r"(a[1]), "r"(a[2]), "r"(a[3]), "r"(b0), "r"(b1), "f"(0.f));
}
__device__ __forceinline__ uint32_t lds32(uint32_t a) {
    uint32_t v;
    asm volatile("ld.shared.u32 %0, [%1];" : "=r"(v) : "r"(a) : "memory");
    return v;
}
__device__ __forceinline__ uint32_t ctl_load(uint32_t a) {
    uint32_t v;
    asm volatile("ld.volatile.shared.u32 %0, [%1];" : "=r"(v) : "r"(a) : "memory");
    return v;
}
__device__ __forceinline__ void ctl_store(uint32_t a, uint32_t v) {
    asm volatile("st.volatile.shared.u32 [%0], %1;" ::"r"(a), "r"(v) : "memory");
}
__device__ __forceinline__ float2 lds64f(uint32_t a) {
    float2 v;
    asm volatile("ld.shared.v2.f32 {%0,%1}, [%2];" : "=f"(v.x), "=f"(v.y) : "r"(a) : "memory");
    return v;
}
__device__ __forceinline__ uint4 lds128(uint32_t a) {
    uint4 v;
    asm volatile("ld.shared.v4.u32 {%0,%1,%2,%3}, [%4];" : "=r"(v.x), "=r"(v.y), "=r"(v.z), "=r"(v.w) : "r"(a) : "memory");
    return v;
}
__device__ __forceinline__ void sts16(uint32_t a, uint32_t v) {
    asm volatile("st.shared.u16 [%0], %1;" ::"r"(a), "h"((unsigned short)v) : "memory");
}
__device__ __forceinline__ void sts32(uint32_t a, uint32_t v) {
    asm volatile("st.shared.u32 [%0], %1;" ::"r"(a), "r"(v) : "memory");
}
__device__ __forceinline__ void sts32f(uint32_t a, float v) {
    asm volatile("st.shared.f32 [%0], %1;" ::"r"(a), "f"(v) : "memory");
}
__device__ __forceinline__ void sts64f(uint32_t a, float x, float y) {
    asm volatile("st.shared.v2.f32 [%0], {%1,%2};" ::"r"(a), "f"(x), "f"(y) : "memory");
}
__device__ __forceinline__ void sts128(uint32_t a, uint4 v) {
    asm volatile("st.shared.v4.u32 [%0], {%1,%2,%3,%4};" ::"r"(a), "r"(v.x), "r"(v.y), "r"(v.z), "r"(v.w) : "memory");
}

constexpr uint32_t EMPTY = 0xffffffffu;
__device__ __forceinline__ void xld32(uint32_t& v, const uint32_t* p, uint32_t empty) {
    asm volatile("{\n.reg .pred p;\nsetp.eq.u32 p, %0, %2;\n@p ld.relaxed.gpu.global.u32 %0, [%1];\n}"
                 : "+r"(v) : "l"(p), "r"(empty) : "memory");
}
__device__ __forceinline__ void xld128(uint4& v, const uint32_t* p, uint32_t top) {
    asm volatile("{\n.reg .pred p;\nsetp.eq.u32 p, %5, 0xffffffff;\n@p ld.relaxed.gpu.global.v4.u32 {%0,%1,%2,%3}, [%4];\n}"
                 : "+r"(v.x), "+r"(v.y), "+r"(v.z), "+r"(v.w) : "l"(p), "r"(top) : "memory");
}
__device__ __forceinline__ void xst32(uint32_t* p, uint32_t v) {
    asm volatile("st.relaxed.gpu.global.u32 [%0], %1;" ::"l"(p), "r"(v) : "memory");
}
__device__ __forceinline__ void xst64(uint32_t* p, uint32_t a, uint32_t b) {
    asm volatile("st.relaxed.gpu.global.v2.u32 [%0], {%1,%2};" ::"l"(p), "r"(a), "r"(b) : "memory");
}
__device__ __forceinline__ uint32_t top_word(const uint4& v) { return max(__vimax3_u32(v.x, v.y, v.z), v.w); }
template <int N, int STRIDE, bool WORD = false>
struct Poll {
    uint4 v[N];
    uint32_t top[N], word, want;
    const uint32_t *src, *wsrc;
    int left;
    __device__ __forceinline__ Poll(const uint32_t* s, uint32_t init, uint32_t init_last, const uint32_t* ws = nullptr,
                                    uint32_t init_word = 0)
        : word(init_word), want(init), src(s), wsrc(ws), left(init ? SPIN_LIMIT : 2) {
#pragma unroll
        for (int i = 0; i < N; i++) {
            top[i] = i == N - 1 ? init_last : init;
            v[i] = make_uint4(top[i], top[i], top[i], top[i]);
        }
    }
    __device__ __forceinline__ void issue() {
#pragma unroll
        for (int i = 0; i < N; i++) xld128(v[i], src + i * STRIDE, top[i]);
        if (WORD) xld32(word, wsrc, EMPTY);
        left--;
    }
    __device__ __forceinline__ bool missing() {
        uint32_t m = WORD ? word : 0;
#pragma unroll
        for (int i = 0; i < N; i++) {
            top[i] = top_word(v[i]);
            m = max(m, top[i]);
        }
        return __any_sync(0xffffffffu, m == want && left > 0);
    }
    __device__ __forceinline__ void until(uint32_t bar) {
#pragma unroll 1
        while (!mbar_test(bar, 0)) {
            issue();
            if (!missing()) break;
        }
        mbar_wait(bar, ~want & 1);
    }
    template <class F>
    __device__ __forceinline__ void finish(F use) {
        bool again;
#pragma unroll 1
        do {
            issue();
            again = missing();
            use();
        } while (again);
    }
};
__device__ __forceinline__ uint32_t poll32(const uint32_t* src, uint32_t init, uint32_t empty) {
    int left = SPIN_LIMIT;
#pragma unroll 1
    do {
        xld32(init, src, empty);
        left--;
    } while (__any_sync(0xffffffffu, init == empty && left > 0));
    return init;
}
__device__ __forceinline__ uint32_t pin(uint32_t v) {
    asm volatile("shfl.sync.bfly.b32 %0, %0, 0, 0x1f, 0xffffffff;" : "+r"(v));
    return v;
}
__device__ __forceinline__ uint32_t bf2_add(uint32_t a, uint32_t b) {
    uint32_t r;
    asm("add.rn.bf16x2 %0, %1, %2;" : "=r"(r) : "r"(a), "r"(b));
    return r;
}
__device__ __forceinline__ uint32_t bf2_relu_sq(uint32_t a) {
    uint32_t r;
    asm("{\n.reg .b32 m;\nmax.bf16x2 m, %1, %2;\nmul.rn.bf16x2 %0, m, m;\n}" : "=r"(r) : "r"(a), "r"(0));
    return r;
}

__device__ __forceinline__ uint32_t pack_bf(float lo, float hi) {
    uint32_t r;
    asm("cvt.rn.bf16x2.f32 %0, %1, %2;" : "=r"(r) : "f"(hi), "f"(lo));
    return r;
}
__device__ __forceinline__ float bf_round(float v) { return __uint_as_float(pack_bf(0.f, v)); }
__device__ __forceinline__ float bf_lo(uint32_t w) { return __uint_as_float(w << 16); }
__device__ __forceinline__ float bf_hi(uint32_t w) { return __uint_as_float(w & 0xffff0000u); }

__device__ __forceinline__ float inv_std(float var) {
    float sd, inv;
    asm("sqrt.approx.ftz.f32 %0, %1;" : "=f"(sd) : "f"(bf_round(var + 1e-5f)));
    asm("rcp.approx.ftz.f32 %0, %1;" : "=f"(inv) : "f"(bf_round(sd)));
    return inv;
}

__device__ __forceinline__ void layernorm_row(const uint32_t (&w)[7], uint32_t dst, int lane) {
    const float shift = bf_lo(__shfl_sync(0xffffffffu, w[0], 0));
    float s = 0.f, ss = 0.f;
#pragma unroll
    for (int i = 0; i < 7; i++) {
        const float a = bf_lo(w[i]) - shift, b = bf_hi(w[i]) - shift;
        s += a + b;
        ss = fmaf(a, a, fmaf(b, b, ss));
    }
#pragma unroll
    for (int o = 16; o; o >>= 1) {
        s += __shfl_xor_sync(0xffffffffu, s, o);
        ss += __shfl_xor_sync(0xffffffffu, ss, o);
    }
    const float md = s * (1.f / DM);
    const float mean = bf_round(shift + md);
    const float inv = inv_std(bf_round(fmaxf(ss * (1.f / DM) - md * md, 0.f)));
#pragma unroll
    for (int i = 0; i < 7; i++) {
        const float a = bf_round(bf_lo(w[i]) - mean) * inv, b = bf_round(bf_hi(w[i]) - mean) * inv;
        sts32(dst + (i * 32 + lane) * 4, pack_bf(a, b));
    }
}

__device__ __forceinline__ void frags_w448(uint32_t (&a)[8][4], uint32_t src, int ew, int lane) {
    const int r = lane & 7, mi = lane >> 3;
    const uint32_t base = src + ((ew < 7 ? ew : 0) * 64 + (mi >> 1) * 8 + r) * 64;
#pragma unroll
    for (int ks = 0; ks < 4; ks++)
#pragma unroll
        for (int mt = 0; mt < 2; mt++)
            ldsm4t(a[ks * 2 + mt], base + ks * 1024 + (((2 * mt + (mi & 1)) ^ (r >> 1)) << 4));
}
__device__ __forceinline__ float2 gemv448(const uint32_t (&a)[8][4], uint32_t sb, int ew, int lane, int et) {
    const int g = lane >> 2, t = lane & 3;
    bar_sync(2, 256);
    if (ew < 7) {
        float c[4][4] = {};
        const uint32_t xb = sb + SM_XN + (g * 228 + ew * 32 + t) * 4;
#pragma unroll
        for (int ks = 0; ks < 4; ks++) {
            const uint32_t b0 = lds32(xb + ks * 32), b1 = lds32(xb + ks * 32 + 16);
            mma(c[(ks & 1) * 2], a[ks * 2], b0, b1);
            mma(c[(ks & 1) * 2 + 1], a[ks * 2 + 1], b0, b1);
        }
        const uint32_t rb = sb + SM_RED + (ew * 288 + t * 72 + g) * 4;
#pragma unroll
        for (int mt = 0; mt < 2; mt++) {
            sts32f(rb + mt * 64, c[mt][0] + c[2 + mt][0]);
            sts32f(rb + mt * 64 + 144, c[mt][1] + c[2 + mt][1]);
            sts32f(rb + mt * 64 + 32, c[mt][2] + c[2 + mt][2]);
            sts32f(rb + mt * 64 + 176, c[mt][3] + c[2 + mt][3]);
        }
    }
    bar_sync(2, 256);
    float2 acc = make_float2(0.f, 0.f);
    if (et < 128) {
        const uint32_t rb = sb + SM_RED + ((et >> 4) * 36 + (et & 15) * 2) * 4;
#pragma unroll
        for (int w = 0; w < 7; w++) {
            const float2 v = lds64f(rb + w * 1152);
            acc.x += v.x;
            acc.y += v.y;
        }
    }
    return acc;
}

struct Params {
    const __nv_bfloat16 *x, *k, *v, *wq, *wo, *w1, *b1, *w2, *b2;
    __nv_bfloat16* out;
    Exchange* xch;
    alignas(64) CUtensorMap map_wo, map_w1, map_w2;
};

__global__ void __launch_bounds__(NTHREADS, 1) fused_decode_kernel(const __grid_constant__ Params p) {
    extern __shared__ __align__(1024) unsigned char smem[];
    const uint32_t sb = (uint32_t)__cvta_generic_to_shared(smem);
    const int tid = threadIdx.x, warp = tid >> 5, lane = tid & 31;
    const int c = blockIdx.x;
    const char* kbase = (const char*)p.k + (size_t)c * (SK * DH * 2);
    const char* vbase = (const char*)p.v + (size_t)c * (SK * DH * 2);

    const int rot = (c * ROT) & (NCH - 1);
    Exchange* const gx = p.xch;
    const bool is_f1 = !(c & 1);
    const int fi = c >> 1;

    if (tid == 128) l2_prefetch(p.wq + c * 14336, 28672, 1);
    if (warp == 4) {
        if (lane == 0) {
#pragma unroll
            for (int s = 0; s < NS; s++) {
                mbar_init(sb + BAR_FULL + 8 * s, 1);
                mbar_init(sb + BAR_EMPTY + 8 * s, 4);
            }
#pragma unroll
            for (int w = 0; w < 8; w++) {
                if (w < 4) mbar_init(sb + BAR_WO + 8 * w, 1);
                mbar_init(sb + BAR_W1 + 8 * w, 1);
            }
            mbar_init(sb + BAR_DRY, 4);
            mbar_init(sb + BAR_WQ, 128);
            mbar_init(sb + BAR_Q, 1);
            mbar_init(sb + BAR_E1, 1);
            mbar_init(sb + BAR_X, 1);
            mbar_init(sb + BAR_X + 8, 1);
            ctl_store(sb + SM_PROG, 0);
            ctl_store(sb + SM_DEPTH, 2);
            asm volatile("fence.mbarrier_init.release.cluster;" ::: "memory");
        }
        __syncthreads();
        if (lane == 0) {
            uint64_t pol;
            asm volatile("createpolicy.fractional.L2::evict_first.b64 %0, 1.0;" : "=l"(pol));
            mbar_expect_tx(sb + BAR_FULL, CHUNK);
            bulk_load(sb + SM_RING, kbase + rot * CHUNK, CHUNK, sb + BAR_FULL, pol);
            spin_or(K1_DELAY, sb + BAR_WQ);
            int s = 1, sl = 0, landed = 0;
            uint32_t ph = 1, phl = 0;
#pragma unroll 1
            for (int i = 1; i <= 2 * NCH; i++) {
                const char* src = (i < NCH ? kbase : vbase) + ((i + rot) & (NCH - 1)) * CHUNK;
                for (int it = 0; landed < (i < 2 * NCH ? i + 1 - (int)ctl_load(sb + SM_DEPTH) : i); it++) {
                    if (mbar_test(sb + BAR_FULL + 8 * sl, phl) || it >= 4 * SPIN_LIMIT) {
                        asm volatile("red.relaxed.gpu.global.add.u32 [%0], 1;" ::"l"(gx->count + 32) : "memory");
                        ctl_store(sb + SM_PROG, ++landed);
                        if (++sl == NS) { sl = 0; phl ^= 1; }
                    } else {
                        __nanosleep(20);
                    }
                }
                if (i == 2 * NCH) break;
                mbar_wait(sb + BAR_EMPTY + 8 * s, ph);
                mbar_expect_tx(sb + BAR_FULL + 8 * s, CHUNK);
                bulk_load(sb + SM_RING + s * CHUNK, src, CHUNK, sb + BAR_FULL + 8 * s, pol);
                if (++s == NS) { s = 0; ph ^= 1; }
            }
        }
    } else if (warp < 4) {
        const int g = lane >> 2, t = lane & 3, r = lane & 7, mi = lane >> 3;
        {
            uint32_t* slot = gx->q + c * 128 + tid;
            uint32_t w = 0;
            xld32(w, slot, 0);
            const int row = tid >> 2, ch = tid & 3;
            const uint32_t dst = sb + SM_WQ + row * 64 + ((ch ^ ((row >> 1) & 3)) << 4);
            const __nv_bfloat16* src = p.wq + row * (NH * DH) + c * 32 + ch * 8;
#pragma unroll
            for (int i = 0; i < 14; i++)
                asm volatile("cp.async.cg.shared.global [%0], [%1], 16;" ::"r"(dst + i * 2048), "l"(src + i * 32 * (NH * DH)) : "memory");
            __syncthreads();
            asm volatile("cp.async.mbarrier.arrive.noinc.shared::cta.b64 [%0];" ::"r"(sb + BAR_WQ) : "memory");
            bar_sync(3, 256);
            w = poll32(slot, w, 0);
            xst32(slot, 0);
            sts32(sb + SM_Q + tid * 4, ~w);
        }
        bar_sync(1, 128);
        asm volatile("fence.proxy.async.shared::cta;" ::: "memory");
        if (tid == 0) mbar_arrive(sb + BAR_Q);
        int s = 0;
        uint32_t ph = 0;
        float rmax = -INFINITY;
        {
            uint32_t qf[32];
#pragma unroll
            for (int i = 0; i < 32; i++) qf[i] = lds32(sb + SM_Q + ((i ^ g) * 4 + t) * 4);
            uint32_t off[4];
#pragma unroll
            for (int i = 0; i < 4; i++)
                off[i] = sb + SM_RING + (warp * 16 + (mi & 1) * 8 + r) * 512 + (((2 * i + (mi >> 1)) ^ r) << 4);
            const bool owner = t == (g >> 1);
            uint32_t pdst = sb + SM_P + (t * 16 + warp * 4 + (g & 1)) * 2;
#pragma unroll 1
            for (int i = 0; i < NCH; i++) {
                mbar_wait(sb + BAR_FULL + 8 * s, ph);
                float acc[4][4] = {};
#pragma unroll
                for (int ks = 0; ks < 16; ks++) {
                    uint32_t a[4];
                    ldsm4(a, off[ks & 3] + s * CHUNK + (ks >> 2) * 128);
                    mma(acc[ks & 3], a, qf[2 * ks], qf[2 * ks + 1]);
                }
                __syncwarp();
                if (lane == 0) mbar_arrive(sb + BAR_EMPTY + 8 * s);
                float v[4];
#pragma unroll
                for (int e = 0; e < 4; e++) v[e] = (acc[0][e] + acc[1][e]) + (acc[2][e] + acc[3][e]);
                const float lo = (g & 1) ? v[1] : v[0], hi = (g & 1) ? v[3] : v[2];
                const uint32_t sc = pack_bf(bf_round(lo) * 0.0625f, bf_round(hi) * 0.0625f);
                if (owner) {
                    sts16(pdst, sc & 0xffffu);
                    sts16(pdst + 4, sc >> 16);
                    rmax = fmaxf(rmax, fmaxf(bf_lo(sc), bf_hi(sc)));
                }
                pdst += 128;
                if (++s == NS) { s = 0; ph ^= 1; }
            }
        }
        {
#pragma unroll
            for (int o = 16; o; o >>= 1) rmax = fmaxf(rmax, __shfl_xor_sync(0xffffffffu, rmax, o));
            if (lane == 0) sts32f(sb + SM_STAT + warp * 4, rmax);
            bar_sync(1, 128);
            const uint4 mx = lds128(sb + SM_STAT);
            const float m = fmaxf(fmaxf(__uint_as_float(mx.x), __uint_as_float(mx.y)),
                                  fmaxf(__uint_as_float(mx.z), __uint_as_float(mx.w)));
            float e[32];
            float sum = 0.f;
#pragma unroll
            for (int i = 0; i < 4; i++) {
                const uint4 w = lds128(sb + SM_P + (i * 128 + tid) * 16);
                const uint32_t ww[4] = {w.x, w.y, w.z, w.w};
#pragma unroll
                for (int j = 0; j < 4; j++) {
                    e[i * 8 + 2 * j] = __expf(bf_lo(ww[j]) - m);
                    e[i * 8 + 2 * j + 1] = __expf(bf_hi(ww[j]) - m);
                    sum += e[i * 8 + 2 * j] + e[i * 8 + 2 * j + 1];
                }
            }
#pragma unroll
            for (int o = 16; o; o >>= 1) sum += __shfl_xor_sync(0xffffffffu, sum, o);
            if (lane == 0) sts32f(sb + SM_STAT + 16 + warp * 4, sum);
            bar_sync(1, 128);
            const uint4 sm = lds128(sb + SM_STAT + 16);
            const float inv = 1.f / ((__uint_as_float(sm.x) + __uint_as_float(sm.y)) +
                                     (__uint_as_float(sm.z) + __uint_as_float(sm.w)));
#pragma unroll
            for (int i = 0; i < 4; i++) {
                uint4 w;
                w.x = pack_bf(e[i * 8 + 0] * inv, e[i * 8 + 1] * inv);
                w.y = pack_bf(e[i * 8 + 2] * inv, e[i * 8 + 3] * inv);
                w.z = pack_bf(e[i * 8 + 4] * inv, e[i * 8 + 5] * inv);
                w.w = pack_bf(e[i * 8 + 6] * inv, e[i * 8 + 7] * inv);
                sts128(sb + SM_P + (i * 128 + tid) * 16, w);
            }
            bar_sync(1, 128);
        }
        {
            uint32_t off[4];
#pragma unroll
            for (int i = 0; i < 4; i++)
                off[i] = sb + SM_RING + ((mi >> 1) * 8 + r) * 512 + warp * 128 + (((2 * i + (mi & 1)) ^ r) << 4);
            const uint32_t pmask = t == (g >> 1) ? ((g & 1) ? 0xffff0000u : 0x0000ffffu) : 0u;
            uint32_t* odst = gx->o + ((c & 15) * 8 + (c >> 4)) * 128 + (warp * 2 + (t >> 1)) * 16 + (g >> 1) * 4 +
                             (t & 1) * 2 + (g & 1);
            uint32_t lane2;
            asm volatile("mov.u32 %0, %%laneid;" : "=r"(lane2));
#pragma unroll 1
            for (int pass = 0; pass < 2; pass++) {
                int n = pass * NCH;
                asm volatile("" : "+r"(n));
                float acc[4][4] = {};
                uint32_t psrc = sb + SM_P + t * 32;
                uint32_t va[8][4], vb[8][4] = {};
                uint32_t pt[4] = {};
                uint32_t cur[4];
#pragma unroll
                for (int j = 0; j < 4; j++) cur[j] = off[j] + s * CHUNK;
                uint32_t bar = sb + BAR_FULL + 8 * s, ready = 0;
#pragma unroll 1
                for (int i = n; i > 0; i--) {
                    if (!ready) mbar_wait(bar, ph);
                    const bool wrap = bar == sb + BAR_FULL + 8 * (NS - 1);
                    const uint32_t barn = wrap ? sb + BAR_FULL : bar + 8;
                    ph ^= wrap;
                    const uint4 p0 = lds128(psrc), p1 = lds128(psrc + 16);
#pragma unroll
                    for (int j = 0; j < 2; j++) ldsm4t(va[j], cur[j & 3] + (j >> 2) * 8192);
                    uint32_t tok;
                    asm volatile("{\n.reg .pred p;\nmbarrier.test_wait.parity.shared::cta.b64 p, [%2], %3;\n"
                                 "selp.u32 %0, 1, 0, p;\nselp.u32 %1, %4, %5, p;\n}"
                                 : "=r"(ready), "=r"(tok) : "r"(barn), "r"(ph), "r"(lane), "r"(lane2) : "memory");
#pragma unroll
                    for (int j = 2; j < 8; j++) ldsm4t(va[j], cur[j & 3] + (j >> 2) * 8192);
#pragma unroll
                    for (int j = 0; j < 8; j++) mma(acc[j & 3], vb[j], pt[(j >> 2) * 2], pt[(j >> 2) * 2 + 1]);
#pragma unroll
                    for (int j = 0; j < 8; j++) ldsm4t(vb[j], cur[j & 3] + (2 + (j >> 2)) * 8192);
                    asm volatile("{\n.reg .pred p;\nsetp.eq.u32 p, %1, 0;\n@p mbarrier.arrive.shared::cta.b64 _, [%0];\n}"
                                 ::"r"(bar + 8 * NS), "r"(tok) : "memory");
                    mma(acc[0], va[0], p0.x & pmask, p0.y & pmask);
                    mma(acc[1], va[1], p0.x & pmask, p0.y & pmask);
                    mma(acc[2], va[2], p0.x & pmask, p0.y & pmask);
                    mma(acc[3], va[3], p0.x & pmask, p0.y & pmask);
                    mma(acc[0], va[4], p0.z & pmask, p0.w & pmask);
                    mma(acc[1], va[5], p0.z & pmask, p0.w & pmask);
                    mma(acc[2], va[6], p0.z & pmask, p0.w & pmask);
                    mma(acc[3], va[7], p0.z & pmask, p0.w & pmask);
                    pt[0] = p1.x & pmask;
                    pt[1] = p1.y & pmask;
                    pt[2] = p1.z & pmask;
                    pt[3] = p1.w & pmask;
                    psrc += 128;
                    bar = barn;
                    const uint32_t step = wrap ? -(NS - 1) * CHUNK : CHUNK;
#pragma unroll
                    for (int j = 0; j < 4; j++) cur[j] += step;
                }
#pragma unroll
                for (int j = 0; j < 8; j++) mma(acc[j & 3], vb[j], pt[(j >> 2) * 2], pt[(j >> 2) * 2 + 1]);
                float ev[4], od[4];
#pragma unroll
                for (int T = 0; T < 4; T++) {
                    ev[T] = acc[T][0] + acc[T][3];
                    od[T] = acc[T][1] + acc[T][2];
                }
                ev[0] += __shfl_xor_sync(0xffffffffu, ev[1], 1);
                od[0] += __shfl_xor_sync(0xffffffffu, od[1], 1);
                ev[2] += __shfl_xor_sync(0xffffffffu, ev[3], 1);
                od[2] += __shfl_xor_sync(0xffffffffu, od[3], 1);
                ev[0] += __shfl_xor_sync(0xffffffffu, ev[2], 2);
                od[0] += __shfl_xor_sync(0xffffffffu, od[2], 2);
                const float other = __shfl_xor_sync(0xffffffffu, (g & 1) ? ev[0] : od[0], 4);
                const uint32_t w = (g & 1) ? pack_bf(other, od[0]) : pack_bf(ev[0], other);
                xst32(odst, n ? w : EMPTY);
                __syncwarp();
                if (!n && lane == 0) mbar_arrive(sb + BAR_DRY);
                if (c < 112) {
                    bar_sync(1, 128);
                    if (tid == 0) {
                        const uint32_t on = n ? 0xffffffffu : 0u;
                        mbar_wait(sb + BAR_W0, ~on & 1);
                        l2_prefetch(p.w1 + c * 7168, 14336, on);
                        spin((is_f1 ? W1_DELAY : PF_DELAY) & on);
                        if (!is_f1) {
                            l2_prefetch(p.w2 + fi * 14336, 28672, on);
                            mbar_wait(sb + BAR_E1, ~on & 1);
                            spin(W2_DELAY & on);
                        }
                        tile_loads(sb + (n ? SM_WX : SM_WO + 8192), is_f1 ? &p.map_w1 : &p.map_w2,
                                   is_f1 ? fi * 32 : (fi % 28) * 16, n ? 0 : 1 << 20, is_f1 ? 64 : 224, is_f1 ? 4096 : 7168,
                                   sb + (n ? BAR_W1 : BAR_X), n ? 8 - is_f1 : 1);
                    }
                }
            }
        }
    } else {
        const int ew = warp - 5, et = tid - 160;
        const int r = lane & 7, mi = lane >> 3;
        {
            uint32_t w[7];
#pragma unroll
            for (int i = 0; i < 7; i++)
                asm volatile("ld.global.nc.u32 %0, [%1];" : "=r"(w[i]) : "l"((const uint32_t*)p.x + ew * 224 + i * 32 + lane));
            __syncthreads();
            layernorm_row(w, sb + SM_XN + ew * 912, lane);
            mbar_wait(sb + BAR_WQ, 0);
            uint32_t a[8][4];
            frags_w448(a, sb + SM_WQ, ew, lane);
            const float2 q = gemv448(a, sb, ew, lane, et);
            if (et < 128) {
                xst32(gx->q + ((et >> 4) * 16 + (c >> 3)) * 128 + (c & 7) * 16 + (et & 15), ~pack_bf(q.x, q.y));
                asm volatile("bar.arrive 3, 256;" ::: "memory");
            }
        }
        const int hh = c / 7, jj = c - hh * 7;
        const int cg = fi % 28, half = fi / 28;
        const int ht0 = (c - 112) * 7 + min(ew, 6);
        uint32_t side;
        asm volatile("ld.global.nc.u32 %0, [%1];" : "=r"(side)
                     : "l"(c < 112 ? (is_f1 ? p.b1 + fi * 32 + (et & 15) * 2 : p.b2 + cg * 16 + r * 2)
                           : p.x + ((ht0 & 6) + (mi & 1)) * DM + (ht0 >> 3) * 32 + (r & 3) * 8 + (ht0 & 1) * 4 + (r >> 2) * 2));
        uint32_t seen_prog = 0;
#pragma unroll 1
        for (int pass = 0; pass < 2; pass++) {
            uint32_t live = pass;
            asm volatile("" : "+r"(live));
            const uint32_t want = 0u - live, wipe = ~want;
            const int et = pin(tid - 160), ew = et >> 5, lane = et & 31;
            const int g = lane >> 2, t = lane & 3, r = lane & 7, mi = lane >> 3;
            if (et == 0) {
                if (!live) mbar_wait(sb + BAR_Q, 0);
#pragma unroll 1
                for (int it = 0; it < SPIN_LIMIT; it++) {
                    const uint32_t prog = ctl_load(sb + SM_PROG);
                    int total = 0;
                    if (prog == seen_prog) __nanosleep(100);
                    if (prog != seen_prog || prog >= 2 * NCH - 8)
                        asm volatile("ld.relaxed.gpu.global.u32 %0, [%1];" : "=r"(total) : "l"(gx->count + 32) : "memory");
                    if (total >= ALL_CHUNKS - LIFT_LEFT) {
                        ctl_store(sb + SM_DEPTH, NS);
                    } else if (prog != seen_prog) {
                        const int lead = prog * NCTA - total;
                        ctl_store(sb + SM_DEPTH, lead >= LEAD1 ? 1 : lead >= LEAD2 ? 2 : lead >= LEAD2 - 128 ? 3 : lead >= LEAD2 - 256 ? 4 : NS);
                    }
                    seen_prog = prog;
                    if (live ? total >= ALL_CHUNKS - (c < 112 ? TRIG_LEFT : 0) : mbar_test(sb + BAR_DRY, 0)) break;
                }
                tile_loads(sb + SM_WO, &p.map_wo, jj * 64, live ? hh * 256 : 1 << 20, 64, 8192, sb + (live ? BAR_WO : BAR_X + 8),
                           c >= 112 ? 0 : live ? 4 : 1);
            } else if (et == 32 && live) {
                uint32_t seen;
                mbar_wait(sb + BAR_DRY, 0);
                asm volatile("atom.release.gpu.global.add.u32 %0, [%1], 1;" : "=r"(seen) : "l"(gx->count) : "memory");
                int it = 0;
                for (seen++; seen < NCTA && ++it < SPIN_LIMIT;) {
                    __nanosleep(512);
                    asm volatile("ld.relaxed.gpu.global.u32 %0, [%1];" : "=r"(seen) : "l"(gx->count) : "memory");
                }
                asm volatile("ld.acquire.gpu.global.u32 %0, [%1];" : "=r"(seen) : "l"(gx->count) : "memory");
            }
            __syncwarp();
            bar_sync(2, 256);
            if (c >= 112) {
                if (ew < 7) {
                    const bool odd = mi & 1;
                    const int ht = (c - 112) * 7 + ew;
                    float a0, a1;
                    uint32_t* const dst = gx->h + pin((((mi >> 1) * 14 + (ht >> 3)) * 8 + (ht & 6) + (mi & 1)) * 16 + (ht & 1) * 8 + r);
                    Poll<4, 128> in(gx->part + pin(ht * 512 + lane * 4), want, want);
                    spin(R_DELAY & want);
                    in.finish([&] {
                        const uint4 (&v)[4] = in.v;
                        const float f0 = (__uint_as_float(v[0].x) + __uint_as_float(v[1].x)) + (__uint_as_float(v[2].x) + __uint_as_float(v[3].x));
                        const float f1 = (__uint_as_float(v[0].y) + __uint_as_float(v[1].y)) + (__uint_as_float(v[2].y) + __uint_as_float(v[3].y));
                        const float f2 = (__uint_as_float(v[0].z) + __uint_as_float(v[1].z)) + (__uint_as_float(v[2].z) + __uint_as_float(v[3].z));
                        const float f3 = (__uint_as_float(v[0].w) + __uint_as_float(v[1].w)) + (__uint_as_float(v[2].w) + __uint_as_float(v[3].w));
                        a0 = (odd ? f1 : f0) + __shfl_xor_sync(0xffffffffu, odd ? f0 : f1, 8);
                        a1 = (odd ? f3 : f2) + __shfl_xor_sync(0xffffffffu, odd ? f2 : f3, 8);
                    });
                    a0 += __shfl_xor_sync(0xffffffffu, a0, 16);
                    a1 += __shfl_xor_sync(0xffffffffu, a1, 16);
                    xst32(dst, bf2_add(side, pack_bf(a0, a1)) | wipe);
                }
                if (!live) bar_sync(5, 256);
                continue;
            }
            {
                const uint32_t fa = pin(sb + SM_WO + ((ew >> 1) * 64 + (mi >> 1) * 8 + r) * 128 + ((((ew & 1) * 4 + (mi & 1)) ^ r) << 4));
                const uint32_t wb = pin(sb + SM_RED + ((ew >> 1) * 544 + t * 136 + (ew & 1) * 64 + g * 2) * 4);
                const uint32_t rb = pin(sb + SM_RED + ((ew & 3) * 136 + ((ew >> 2) * 32 + (r >> 1) * 8 + mi * 2 + (r & 1)) * 2) * 4);
                uint32_t* const pdst = gx->part + pin((((jj * 8 + ew) * 2 + (lane >> 4)) * 16 + hh) * 32 + (lane & 15) * 2);
                Poll<2, 16> in(gx->o + pin((hh * 8 + g) * 128 + (ew >> 1) * 32 + t * 4), want, want);
                spin_or(O_DELAY & want, sb + BAR_WO + 8 * (ew >> 1));
                in.until(sb + BAR_WO + 8 * (ew >> 1));
                uint32_t a[8][4];
#pragma unroll
                for (int i = 0; i < 4; i++) {
                    const int ks = (i >> 1) + (i & 1) * 2;
                    ldsm4t(a[ks * 2], fa + ks * 2048);
                    ldsm4t(a[ks * 2 + 1], (fa ^ 32) + ks * 2048);
                }
                float acc[2][2][4];
                in.finish([&] {
#pragma unroll
                    for (int i = 0; i < 2; i++) {
                        mma0(acc[i][0], a[i * 4], in.v[i].x, in.v[i].y);
                        mma0(acc[i][1], a[i * 4 + 1], in.v[i].x, in.v[i].y);
                    }
#pragma unroll
                    for (int mt = 0; mt < 2; mt++) {
                        mma(acc[0][mt], a[2 + mt], in.v[0].z, in.v[0].w);
                        mma(acc[1][mt], a[6 + mt], in.v[1].z, in.v[1].w);
                    }
                });
#pragma unroll
                for (int mt = 0; mt < 2; mt++) {
                    sts64f(wb + mt * 128, acc[0][mt][0] + acc[1][mt][0], acc[0][mt][1] + acc[1][mt][1]);
                    sts64f(wb + mt * 128 + 64, acc[0][mt][2] + acc[1][mt][2], acc[0][mt][3] + acc[1][mt][3]);
                }
                bar_sync(2, 256);
                float2 v[4];
#pragma unroll
                for (int w = 0; w < 4; w++) v[w] = lds64f(rb + w * 2176);
                const float s0 = (v[0].x + v[1].x) + (v[2].x + v[3].x);
                const float s1 = (v[0].y + v[1].y) + (v[2].y + v[3].y);
                xst64(pdst, __float_as_uint(s0) | wipe, __float_as_uint(s1) | wipe);
            }
            if (et == 0 && live) mbar_arrive(sb + BAR_E1);
            const uint32_t wbar = sb + BAR_W1 + 8 * ew;
            if (is_f1) {
                constexpr uint32_t ONES = 0x3f803f80u;
                if (ew < 7) {
                    const int b = (et >> 4) & 7, pr = et & 15;
                    const uint32_t fa = pin(sb + SM_WX + (ew * 64 + (mi >> 1) * 8 + r) * 64 + (((mi & 1) ^ (r >> 1)) << 4));
                    const uint32_t wb = pin(sb + SM_RED + (ew * 288 + t * 72 + g) * 4);
                    const uint32_t sw = pin(sb + SM_RED + (ew * 288 + g * 36 + (t == (g >> 1) ? 32 : 34)) * 4);
                    const uint32_t rs = pin(sb + SM_RED + b * 144 + 128), rz = pin(sb + SM_RED + b * 144 + pr * 8);
                    const uint32_t cw = pin(sb + SM_XN + (ew * 32 + g + (t >> 1) * 16 + (t & 1) * 8) * 4), cr = pin(sb + SM_XN + pr * 8);
                    const bool odd = pin(g & 1);
                    uint32_t* const dst = gx->r + pin((((b >> 2) * 56 + fi) * 4 + (b & 3)) * 16 + (pr & 3) * 4 + (pr >> 2));
                    Poll<2, 128> in(gx->h + pin(((fi & 1) * 14 + ew * 2) * 128 + lane * 4), want, want);
                    mbar_wait(wbar, wipe & 1);
                    uint32_t a[8][4];
#pragma unroll
                    for (int ks = 0; ks < 4; ks++) {
                        ldsm4t(a[ks * 2], fa + ks * 1024);
                        ldsm4t(a[ks * 2 + 1], (fa ^ 32) + ks * 1024);
                    }
                    float cs[2][4] = {}, z[2][2][4], st[2][4];
#pragma unroll
                    for (int ks = 0; ks < 4; ks++) {
                        mma(cs[0], a[ks * 2], ONES, ONES);
                        mma(cs[1], a[ks * 2 + 1], ONES, ONES);
                    }
                    sts32f(cw, (t & 1) ? ((t & 2) ? cs[1][2] : cs[0][2]) : ((t & 2) ? cs[1][0] : cs[0][0]));
                    bar_sync(4, 224);
                    float2 cv[7];
#pragma unroll
                    for (int w = 0; w < 7; w++) cv[w] = lds64f(cr + w * 128);
                    const float cs0 = ((cv[0].x + cv[1].x) + (cv[2].x + cv[3].x)) + ((cv[4].x + cv[5].x) + cv[6].x);
                    const float cs1 = ((cv[0].y + cv[1].y) + (cv[2].y + cv[3].y)) + ((cv[4].y + cv[5].y) + cv[6].y);
                    in.finish([&] {
#pragma unroll
                        for (int i = 0; i < 2; i++) {
                            const uint32_t sa[4] = {in.v[i].x, ONES, in.v[i].y, ONES};
                            mma0(z[i][0], a[i * 4], in.v[i].x, in.v[i].y);
                            mma0(z[i][1], a[i * 4 + 1], in.v[i].x, in.v[i].y);
                            mma0(st[i], sa, in.v[i].x, in.v[i].y);
                        }
                    });
#pragma unroll
                    for (int i = 0; i < 2; i++) mma(z[i][0], a[i * 4 + 2], in.v[i].z, in.v[i].w);
#pragma unroll
                    for (int i = 0; i < 2; i++) mma(z[i][1], a[i * 4 + 3], in.v[i].z, in.v[i].w);
#pragma unroll
                    for (int i = 0; i < 2; i++) {
                        const uint32_t sa[4] = {in.v[i].z, ONES, in.v[i].w, ONES};
                        mma(st[i], sa, in.v[i].z, in.v[i].w);
                    }
#pragma unroll
                    for (int mt = 0; mt < 2; mt++) {
                        sts32f(wb + mt * 64, z[0][mt][0] + z[1][mt][0]);
                        sts32f(wb + mt * 64 + 144, z[0][mt][1] + z[1][mt][1]);
                        sts32f(wb + mt * 64 + 32, z[0][mt][2] + z[1][mt][2]);
                        sts32f(wb + mt * 64 + 176, z[0][mt][3] + z[1][mt][3]);
                    }
                    sts64f(sw, odd ? st[0][3] + st[1][3] : st[0][2] + st[1][2], odd ? st[0][1] + st[1][1] : st[0][0] + st[1][0]);
                    bar_sync(4, 224);
                    if (ew < 4) {
                        float2 sv[7], zv[7];
#pragma unroll
                        for (int w = 0; w < 7; w++) sv[w] = lds64f(rs + w * 1152);
#pragma unroll
                        for (int w = 0; w < 7; w++) zv[w] = lds64f(rz + w * 1152);
                        const float mu = (((sv[0].x + sv[1].x) + (sv[2].x + sv[3].x)) + ((sv[4].x + sv[5].x) + sv[6].x)) * (1.f / DM);
                        const float sq = ((sv[0].y + sv[1].y) + (sv[2].y + sv[3].y)) + ((sv[4].y + sv[5].y) + sv[6].y);
                        const float inv = inv_std(bf_round(fmaxf(fmaf(sq, 1.f / DM, -mu * mu), 0.f)));
                        const float mean = bf_round(mu);
                        const float z0 = ((zv[0].x + zv[1].x) + (zv[2].x + zv[3].x)) + ((zv[4].x + zv[5].x) + zv[6].x);
                        const float z1 = ((zv[0].y + zv[1].y) + (zv[2].y + zv[3].y)) + ((zv[4].y + zv[5].y) + zv[6].y);
                        const uint32_t u = pack_bf(fmaf(-mean, cs0, z0) * inv, fmaf(-mean, cs1, z1) * inv);
                        xst32(dst, bf2_relu_sq(bf2_add(u, side)) | wipe);
                    }
                }
            } else {
                const uint32_t fa = pin(sb + SM_WX + (ew * 224 + (mi >> 1) * 8 + r) * 32 + (((mi & 1) ^ (r >> 2)) << 4));
                const uint32_t wb = pin(sb + SM_XN + (ew * 160 + (t & 1) * 80 + (g >> 1) * 4 + (t >> 1) * 2 + (g & 1)) * 4);
                const uint32_t rb = pin(sb + SM_XN + (mi * 40 + r * 4) * 4);
                const bool upper = pin(t >> 1), first = pin(ew == 0);
                uint32_t* const dst = (live ? (uint32_t*)p.out : gx->sink) + pin((half * 4 + mi) * 224 + cg * 8 + r);
                Poll<4, 128, true> in(gx->r + pin((half * 56 + ew * 7) * 64 + lane * 4), want, lane < 16 ? want : 0u,
                                      gx->h + pin((((fi & 1) * 14 + (cg >> 1)) * 8 + half * 4 + mi) * 16 + (r & 3) * 4 +
                                                  (cg & 1) * 2 + (r >> 2)),
                                      ew == 0 ? want : 0u);
                mbar_wait(wbar, wipe & 1);
                uint32_t a[14][4];
#pragma unroll
                for (int ks = 0; ks < 14; ks++) ldsm4t(a[ks], fa + ks * 512);
                float acc[4][4];
                const auto step = [&](int i) {
                    mma(acc[0], a[4 * i], in.v[i].x, in.v[i].y);
                    mma(acc[1], a[4 * i + 1], in.v[i].z, in.v[i].w);
                    if (i < 3) {
                        mma(acc[2], a[4 * i + 2], in.v[i].x, in.v[i].y);
                        mma(acc[3], a[4 * i + 3], in.v[i].z, in.v[i].w);
                    }
                };
                in.finish([&] {
                    mma0(acc[0], a[0], in.v[0].x, in.v[0].y);
                    mma0(acc[1], a[1], in.v[0].z, in.v[0].w);
                    mma0(acc[2], a[2], in.v[0].x, in.v[0].y);
                    mma0(acc[3], a[3], in.v[0].z, in.v[0].w);
                    step(1);
                });
                step(2);
                step(3);
                sts32f(wb, upper ? acc[2][0] + acc[3][0] : acc[0][0] + acc[1][0]);
                sts32f(wb + 160, upper ? acc[2][1] + acc[3][1] : acc[0][1] + acc[1][1]);
                sts32f(wb + 64, upper ? acc[2][2] + acc[3][2] : acc[0][2] + acc[1][2]);
                sts32f(wb + 224, upper ? acc[2][3] + acc[3][3] : acc[0][3] + acc[1][3]);
                bar_sync(2, 256);
                if (first) {
                    float x[8], y[8];
#pragma unroll
                    for (int w = 0; w < 8; w++) {
                        const uint4 q = lds128(rb + w * 640);
                        x[w] = __uint_as_float(q.x) + __uint_as_float(q.z);
                        y[w] = __uint_as_float(q.y) + __uint_as_float(q.w);
                    }
                    const float s0 = ((x[0] + x[1]) + (x[2] + x[3])) + ((x[4] + x[5]) + (x[6] + x[7]));
                    const float s1 = ((y[0] + y[1]) + (y[2] + y[3])) + ((y[4] + y[5]) + (y[6] + y[7]));
                    *dst = bf2_add(in.word, bf2_add(pack_bf(s0, s1), side));
                    asm volatile("{\n.reg .pred p;\nsetp.ne.u32 p, %0, 0;\n@p exit;\n}" ::"r"(live) : "memory");
                } else if (fi == 0 && et == 32 && live) {
                    xst32(gx->count, 0);
                    xst32(gx->count + 32, 0);
                }
            }
            if (!live) bar_sync(5, 256);
        }
    }
}

using EncodeFn = CUresult (*)(CUtensorMap*, CUtensorMapDataType, cuuint32_t, void*, const cuuint64_t*, const cuuint64_t*,
                              const cuuint32_t*, const cuuint32_t*, CUtensorMapInterleave, CUtensorMapSwizzle,
                              CUtensorMapL2promotion, CUtensorMapFloatOOBfill);

void encode_map(EncodeFn fn, CUtensorMap* map, const void* base, int rows, int cols, int box_rows, int box_cols,
                CUtensorMapSwizzle swizzle) {
    const cuuint64_t dims[2] = {(cuuint64_t)cols, (cuuint64_t)rows};
    const cuuint64_t strides[1] = {(cuuint64_t)cols * 2};
    const cuuint32_t box[2] = {(cuuint32_t)box_cols, (cuuint32_t)box_rows};
    const cuuint32_t steps[2] = {1, 1};
    fn(map, CU_TENSOR_MAP_DATA_TYPE_BFLOAT16, 2, const_cast<void*>(base), dims, strides, box, steps,
       CU_TENSOR_MAP_INTERLEAVE_NONE, swizzle, CU_TENSOR_MAP_L2_PROMOTION_L2_128B, CU_TENSOR_MAP_FLOAT_OOB_FILL_NONE);
}

}

extern "C" void kernel_launch(void* const* d_in, const int* in_sizes, int n_in, void* d_out, int out_size) {
    (void)in_sizes; (void)n_in; (void)out_size;
    Params p;
    p.x = (const __nv_bfloat16*)d_in[0];
    p.k = (const __nv_bfloat16*)d_in[1];
    p.v = (const __nv_bfloat16*)d_in[2];
    p.wq = (const __nv_bfloat16*)d_in[3];
    p.wo = (const __nv_bfloat16*)d_in[4];
    p.w1 = (const __nv_bfloat16*)d_in[6];
    p.b1 = (const __nv_bfloat16*)d_in[7];
    p.w2 = (const __nv_bfloat16*)d_in[8];
    p.b2 = (const __nv_bfloat16*)d_in[9];
    p.out = (__nv_bfloat16*)d_out;
    cudaGetSymbolAddress((void**)&p.xch, g_x);
    void* fn = nullptr;
    cudaDriverEntryPointQueryResult found;
    cudaGetDriverEntryPoint("cuTensorMapEncodeTiled", &fn, cudaEnableDefault, &found);
    encode_map((EncodeFn)fn, &p.map_wo, p.wo, NH * DH, DM, 64, 64, CU_TENSOR_MAP_SWIZZLE_128B);
    encode_map((EncodeFn)fn, &p.map_w1, p.w1, DM, FF, 64, 32, CU_TENSOR_MAP_SWIZZLE_64B);
    encode_map((EncodeFn)fn, &p.map_w2, p.w2, FF, DM, 224, 16, CU_TENSOR_MAP_SWIZZLE_32B);
    cudaFuncSetAttribute(fused_decode_kernel, cudaFuncAttributeMaxDynamicSharedMemorySize, SM_TOTAL);
    fused_decode_kernel<<<NCTA, NTHREADS, SM_TOTAL>>>(p);
}
```

```cpp
#include <cuda.h>
#include <cuda_runtime.h>
#include <cuda_bf16.h>
#include <stdint.h>

namespace {

constexpr int DM = 448, NH = 16, SK = 4096, DH = 256, FF = 1792;
constexpr int NCTA = 128;
constexpr int CHUNK = 32768;
constexpr int NCH = SK / 64;
constexpr int NS = 5;
constexpr int ALL_CHUNKS = NCTA * 2 * NCH;
constexpr int LEAD1 = 128;
constexpr int LEAD2 = -128;
constexpr int LIFT_LEFT = 370;
constexpr int TRIG_LEFT = 220;
constexpr int K1_DELAY = 1000;
constexpr int W1_DELAY = 600;
constexpr int PF_DELAY = 500;
constexpr int W2_DELAY = 600;
constexpr int ROT = 32;
constexpr int R_DELAY = 200;
constexpr int O_DELAY = 1600;
constexpr int NTHREADS = 13 * 32;
constexpr int SPIN_LIMIT = 1 << 18;
constexpr int WAIT_LIMIT = 1 << 14;

constexpr int SM_RING = 0;
constexpr int SM_WX = 0;
constexpr int SM_WQ = NS * CHUNK;
constexpr int SM_WO = SM_WQ;
constexpr int SM_P = SM_WQ + 32768;
constexpr int SM_RED = SM_P + 8192;
constexpr int SM_XN = SM_RED + 4 * 544 * 4;
constexpr int SM_Q = SM_XN + 8 * 456 * 2;
constexpr int SM_STAT = SM_Q + 512;
constexpr int SM_PROG = SM_STAT + 32, SM_DEPTH = SM_STAT + 36;
constexpr int SM_BAR = SM_STAT + 64;
constexpr int BAR_FULL = SM_BAR, BAR_EMPTY = BAR_FULL + 8 * NS, BAR_WO = BAR_EMPTY + 8 * NS, BAR_DRY = BAR_WO + 32,
              BAR_WQ = BAR_DRY + 8, BAR_Q = BAR_WQ + 8, BAR_W0 = BAR_WO + 24, BAR_E1 = BAR_Q + 8, BAR_X = BAR_E1 + 8,
              BAR_W1 = BAR_X + 16;
constexpr int SM_TOTAL = BAR_W1 + 64;
static_assert(SM_TOTAL <= 232448, "shared memory budget");

struct Exchange {
    uint32_t q[NCTA * 128];
    uint32_t o[NH * 8 * 128];
    uint32_t part[14 * 8 * 16 * 32];
    uint32_t h[2 * 14 * 8 * 16];
    uint32_t r[2 * 56 * 4 * 16];
    uint32_t count[64];
    uint32_t sink[8 * 224];
};
__device__ __align__(128) Exchange g_x;

__device__ __forceinline__ void mbar_init(uint32_t bar, uint32_t count) {
    asm volatile("mbarrier.init.shared::cta.b64 [%0], %1;" ::"r"(bar), "r"(count) : "memory");
}
__device__ __forceinline__ void mbar_arrive(uint32_t bar) {
    asm volatile("mbarrier.arrive.shared::cta.b64 _, [%0];" ::"r"(bar) : "memory");
}
__device__ __forceinline__ void mbar_expect_tx(uint32_t bar, uint32_t bytes) {
    asm volatile("mbarrier.arrive.expect_tx.shared::cta.b64 _, [%0], %1;" ::"r"(bar), "r"(bytes) : "memory");
}
__device__ __forceinline__ void mbar_wait(uint32_t bar, uint32_t parity) {
    asm volatile("{\n.reg .pred p, q;\n.reg .u32 n;\nmov.u32 n, %2;\n"
                 "RETRY:\nsub.u32 n, n, 1;\nsetp.ne.u32 q, n, 0;\n"
                 "mbarrier.try_wait.parity.shared::cta.b64 p, [%0], %1;\nand.pred q, q, !p;\n@q bra RETRY;\n}"
                 ::"r"(bar), "r"(parity), "n"(WAIT_LIMIT) : "memory");
}
__device__ __forceinline__ uint32_t mbar_test(uint32_t bar, uint32_t parity) {
    uint32_t done;
    asm volatile("{\n.reg .pred p;\nmbarrier.test_wait.parity.shared::cta.b64 p, [%1], %2;\nselp.u32 %0, 1, 0, p;\n}"
                 : "=r"(done) : "r"(bar), "r"(parity) : "memory");
    return done;
}
__device__ __forceinline__ void exit_if(uint32_t on) {
    asm volatile("{\n.reg .pred p;\nsetp.ne.u32 p, %0, 0;\n@p exit;\n}" ::"r"(on) : "memory");
}
__device__ __forceinline__ void spin(uint32_t cycles) {
    const uint32_t t0 = (uint32_t)clock();
    do {
    } while ((uint32_t)clock() - t0 < cycles);
}
__device__ __forceinline__ void spin_or(uint32_t cycles, uint32_t bar) {
    const uint32_t t0 = (uint32_t)clock();
    do {
    } while (!mbar_test(bar, 0) && (uint32_t)clock() - t0 < cycles);
}
__device__ __forceinline__ void l2_prefetch(const void* src, uint32_t bytes, uint32_t on) {
    asm volatile("{\n.reg .pred p;\nsetp.ne.u32 p, %2, 0;\n@p cp.async.bulk.prefetch.L2.global [%0], %1;\n}"
                 ::"l"(src), "r"(bytes), "r"(on) : "memory");
}
__device__ __forceinline__ void bulk_load(uint32_t dst, const void* src, uint32_t bytes, uint32_t bar, uint64_t pol) {
    asm volatile("cp.async.bulk.shared::cluster.global.mbarrier::complete_tx::bytes.L2::cache_hint [%0], [%1], %2, [%3], %4;"
                 ::"r"(dst), "l"(src), "r"(bytes), "r"(bar), "l"(pol) : "memory");
}
__device__ __forceinline__ void tile_loads(uint32_t dst, const CUtensorMap* map, int col, int row, int rows, uint32_t bytes,
                                           uint32_t bar, int n) {
#pragma unroll 1
    for (int i = 0; i < n; i++, dst += bytes, row += rows, bar += 8) {
        mbar_expect_tx(bar, bytes);
        asm volatile("cp.async.bulk.tensor.2d.shared::cluster.global.mbarrier::complete_tx::bytes [%0], [%1, {%2, %3}], [%4];"
                     ::"r"(dst), "l"(map), "r"(col), "r"(row), "r"(bar) : "memory");
    }
}
__device__ __forceinline__ void bar_sync(int id, int n) { asm volatile("bar.sync %0, %1;" ::"r"(id), "r"(n) : "memory"); }

__device__ __forceinline__ void ldsm4(uint32_t (&r)[4], uint32_t a) {
    asm volatile("ldmatrix.sync.aligned.m8n8.x4.shared.b16 {%0,%1,%2,%3}, [%4];"
                 : "=r"(r[0]), "=r"(r[1]), "=r"(r[2]), "=r"(r[3]) : "r"(a) : "memory");
}
__device__ __forceinline__ void ldsm4t(uint32_t (&r)[4], uint32_t a) {
    asm volatile("ldmatrix.sync.aligned.m8n8.x4.trans.shared.b16 {%0,%1,%2,%3}, [%4];"
                 : "=r"(r[0]), "=r"(r[1]), "=r"(r[2]), "=r"(r[3]) : "r"(a) : "memory");
}
__device__ __forceinline__ void mma(float (&c)[4], const uint32_t (&a)[4], uint32_t b0, uint32_t b1) {
    asm volatile("mma.sync.aligned.m16n8k16.row.col.f32.bf16.bf16.f32 {%0,%1,%2,%3}, {%4,%5,%6,%7}, {%8,%9}, {%0,%1,%2,%3};"
                 : "+f"(c[0]), "+f"(c[1]), "+f"(c[2]), "+f"(c[3])
                 : "r"(a[0]), "r"(a[1]), "r"(a[2]), "r"(a[3]), "r"(b0), "r"(b1));
}
__device__ __forceinline__ void mma0(float (&c)[4], const uint32_t (&a)[4], uint32_t b0, uint32_t b1) {
    asm volatile("mma.sync.aligned.m16n8k16.row.col.f32.bf16.bf16.f32 {%0,%1,%2,%3}, {%4,%5,%6,%7}, {%8,%9}, {%10,%10,%10,%10};"
                 : "=f"(c[0]), "=f"(c[1]), "=f"(c[2]), "=f"(c[3])
                 : "r"(a[0]), "r"(a[1]), "r"(a[2]), "r"(a[3]), "r"(b0), "r"(b1), "f"(0.f));
}
__device__ __forceinline__ uint32_t lds32(uint32_t a) {
    uint32_t v;
    asm volatile("ld.shared.u32 %0, [%1];" : "=r"(v) : "r"(a) : "memory");
    return v;
}
__device__ __forceinline__ uint32_t ctl_load(uint32_t a) {
    uint32_t v;
    asm volatile("ld.volatile.shared.u32 %0, [%1];" : "=r"(v) : "r"(a) : "memory");
    return v;
}
__device__ __forceinline__ void ctl_store(uint32_t a, uint32_t v) {
    asm volatile("st.volatile.shared.u32 [%0], %1;" ::"r"(a), "r"(v) : "memory");
}
__device__ __forceinline__ float2 lds64f(uint32_t a) {
    float2 v;
    asm volatile("ld.shared.v2.f32 {%0,%1}, [%2];" : "=f"(v.x), "=f"(v.y) : "r"(a) : "memory");
    return v;
}
__device__ __forceinline__ uint4 lds128(uint32_t a) {
    uint4 v;
    asm volatile("ld.shared.v4.u32 {%0,%1,%2,%3}, [%4];" : "=r"(v.x), "=r"(v.y), "=r"(v.z), "=r"(v.w) : "r"(a) : "memory");
    return v;
}
__device__ __forceinline__ void sts16(uint32_t a, uint32_t v) {
    asm volatile("st.shared.u16 [%0], %1;" ::"r"(a), "h"((unsigned short)v) : "memory");
}
__device__ __forceinline__ void sts32(uint32_t a, uint32_t v) {
    asm volatile("st.shared.u32 [%0], %1;" ::"r"(a), "r"(v) : "memory");
}
__device__ __forceinline__ void sts32f(uint32_t a, float v) {
    asm volatile("st.shared.f32 [%0], %1;" ::"r"(a), "f"(v) : "memory");
}
__device__ __forceinline__ void sts64f(uint32_t a, float x, float y) {
    asm volatile("st.shared.v2.f32 [%0], {%1,%2};" ::"r"(a), "f"(x), "f"(y) : "memory");
}
__device__ __forceinline__ void sts128(uint32_t a, uint4 v) {
    asm volatile("st.shared.v4.u32 [%0], {%1,%2,%3,%4};" ::"r"(a), "r"(v.x), "r"(v.y), "r"(v.z), "r"(v.w) : "memory");
}

constexpr uint32_t EMPTY = 0xffffffffu;
__device__ __forceinline__ void xld32(uint32_t& v, const uint32_t* p, uint32_t empty) {
    asm volatile("{\n.reg .pred p;\nsetp.eq.u32 p, %0, %2;\n@p ld.relaxed.gpu.global.u32 %0, [%1];\n}"
                 : "+r"(v) : "l"(p), "r"(empty) : "memory");
}
__device__ __forceinline__ void xld128(uint4& v, const uint32_t* p, uint32_t top) {
    asm volatile("{\n.reg .pred p;\nsetp.eq.u32 p, %5, 0xffffffff;\n@p ld.relaxed.gpu.global.v4.u32 {%0,%1,%2,%3}, [%4];\n}"
                 : "+r"(v.x), "+r"(v.y), "+r"(v.z), "+r"(v.w) : "l"(p), "r"(top) : "memory");
}
__device__ __forceinline__ void xst32(uint32_t* p, uint32_t v) {
    asm volatile("st.relaxed.gpu.global.u32 [%0], %1;" ::"l"(p), "r"(v) : "memory");
}
__device__ __forceinline__ void xst64(uint32_t* p, uint32_t a, uint32_t b) {
    asm volatile("st.relaxed.gpu.global.v2.u32 [%0], {%1,%2};" ::"l"(p), "r"(a), "r"(b) : "memory");
}
__device__ __forceinline__ uint32_t top_word(const uint4& v) { return max(__vimax3_u32(v.x, v.y, v.z), v.w); }
template <int N, int STRIDE, bool WORD = false>
struct Poll {
    uint4 v[N];
    uint32_t top[N], word, want;
    const uint32_t *src, *wsrc;
    int left;
    __device__ __forceinline__ Poll(const uint32_t* s, uint32_t init, uint32_t init_last, const uint32_t* ws = nullptr,
                                    uint32_t init_word = 0)
        : word(init_word), want(init), src(s), wsrc(ws), left(init ? SPIN_LIMIT : 2) {
#pragma unroll
        for (int i = 0; i < N; i++) {
            top[i] = i == N - 1 ? init_last : init;
            v[i] = make_uint4(top[i], top[i], top[i], top[i]);
        }
    }
    __device__ __forceinline__ void issue() {
#pragma unroll
        for (int i = 0; i < N; i++) xld128(v[i], src + i * STRIDE, top[i]);
        if (WORD) xld32(word, wsrc, EMPTY);
        left--;
    }
    __device__ __forceinline__ bool missing() {
        uint32_t m = WORD ? word : 0;
#pragma unroll
        for (int i = 0; i < N; i++) {
            top[i] = top_word(v[i]);
            m = max(m, top[i]);
        }
        return __any_sync(0xffffffffu, m == want && left > 0);
    }
    __device__ __forceinline__ void until(uint32_t bar) {
#pragma unroll 1
        while (!mbar_test(bar, 0)) {
            issue();
            if (!missing()) break;
        }
        mbar_wait(bar, ~want & 1);
    }
    template <class F>
    __device__ __forceinline__ void finish(F use) {
        bool again;
#pragma unroll 1
        do {
            issue();
            again = missing();
            use();
        } while (again);
    }
};
__device__ __forceinline__ uint32_t poll32(const uint32_t* src, uint32_t init, uint32_t empty) {
    int left = SPIN_LIMIT;
#pragma unroll 1
    do {
        xld32(init, src, empty);
        left--;
    } while (__any_sync(0xffffffffu, init == empty && left > 0));
    return init;
}
__device__ __forceinline__ uint32_t pin(uint32_t v) {
    asm volatile("shfl.sync.bfly.b32 %0, %0, 0, 0x1f, 0xffffffff;" : "+r"(v));
    return v;
}
__device__ __forceinline__ uint32_t bf2_add(uint32_t a, uint32_t b) {
    uint32_t r;
    asm("add.rn.bf16x2 %0, %1, %2;" : "=r"(r) : "r"(a), "r"(b));
    return r;
}
__device__ __forceinline__ uint32_t bf2_relu_sq(uint32_t a) {
    uint32_t r;
    asm("{\n.reg .b32 m;\nmax.bf16x2 m, %1, %2;\nmul.rn.bf16x2 %0, m, m;\n}" : "=r"(r) : "r"(a), "r"(0));
    return r;
}

__device__ __forceinline__ uint32_t pack_bf(float lo, float hi) {
    uint32_t r;
    asm("cvt.rn.bf16x2.f32 %0, %1, %2;" : "=r"(r) : "f"(hi), "f"(lo));
    return r;
}
__device__ __forceinline__ float bf_round(float v) { return __uint_as_float(pack_bf(0.f, v)); }
__device__ __forceinline__ float bf_lo(uint32_t w) { return __uint_as_float(w << 16); }
__device__ __forceinline__ float bf_hi(uint32_t w) { return __uint_as_float(w & 0xffff0000u); }

__device__ __forceinline__ float inv_std(float var) {
    float sd, inv;
    asm("sqrt.approx.ftz.f32 %0, %1;" : "=f"(sd) : "f"(bf_round(var + 1e-5f)));
    asm("rcp.approx.ftz.f32 %0, %1;" : "=f"(inv) : "f"(bf_round(sd)));
    return inv;
}

__device__ __forceinline__ void layernorm_row(const uint32_t (&w)[7], uint32_t dst, int lane) {
    const float shift = bf_lo(__shfl_sync(0xffffffffu, w[0], 0));
    float s = 0.f, ss = 0.f;
#pragma unroll
    for (int i = 0; i < 7; i++) {
        const float a = bf_lo(w[i]) - shift, b = bf_hi(w[i]) - shift;
        s += a + b;
        ss = fmaf(a, a, fmaf(b, b, ss));
    }
#pragma unroll
    for (int o = 16; o; o >>= 1) {
        s += __shfl_xor_sync(0xffffffffu, s, o);
        ss += __shfl_xor_sync(0xffffffffu, ss, o);
    }
    const float md = s * (1.f / DM);
    const float mean = bf_round(shift + md);
    const float inv = inv_std(bf_round(fmaxf(ss * (1.f / DM) - md * md, 0.f)));
#pragma unroll
    for (int i = 0; i < 7; i++) {
        const float a = bf_round(bf_lo(w[i]) - mean) * inv, b = bf_round(bf_hi(w[i]) - mean) * inv;
        sts32(dst + (i * 32 + lane) * 4, pack_bf(a, b));
    }
}

__device__ __forceinline__ void frags_w448(uint32_t (&a)[8][4], uint32_t src, int ew, int lane) {
    const int r = lane & 7, mi = lane >> 3;
    const uint32_t base = src + ((ew < 7 ? ew : 0) * 64 + (mi >> 1) * 8 + r) * 64;
#pragma unroll
    for (int ks = 0; ks < 4; ks++)
#pragma unroll
        for (int mt = 0; mt < 2; mt++)
            ldsm4t(a[ks * 2 + mt], base + ks * 1024 + (((2 * mt + (mi & 1)) ^ (r >> 1)) << 4));
}
__device__ __forceinline__ float2 gemv448(const uint32_t (&a)[8][4], uint32_t sb, int ew, int lane, int et) {
    const int g = lane >> 2, t = lane & 3;
    bar_sync(2, 256);
    if (ew < 7) {
        float c[4][4] = {};
        const uint32_t xb = sb + SM_XN + (g * 228 + ew * 32 + t) * 4;
#pragma unroll
        for (int ks = 0; ks < 4; ks++) {
            const uint32_t b0 = lds32(xb + ks * 32), b1 = lds32(xb + ks * 32 + 16);
            mma(c[(ks & 1) * 2], a[ks * 2], b0, b1);
            mma(c[(ks & 1) * 2 + 1], a[ks * 2 + 1], b0, b1);
        }
        const uint32_t rb = sb + SM_RED + (ew * 288 + t * 72 + g) * 4;
#pragma unroll
        for (int mt = 0; mt < 2; mt++) {
            sts32f(rb + mt * 64, c[mt][0] + c[2 + mt][0]);
            sts32f(rb + mt * 64 + 144, c[mt][1] + c[2 + mt][1]);
            sts32f(rb + mt * 64 + 32, c[mt][2] + c[2 + mt][2]);
            sts32f(rb + mt * 64 + 176, c[mt][3] + c[2 + mt][3]);
        }
    }
    bar_sync(2, 256);
    float2 acc = make_float2(0.f, 0.f);
    if (et < 128) {
        const uint32_t rb = sb + SM_RED + ((et >> 4) * 36 + (et & 15) * 2) * 4;
#pragma unroll
        for (int w = 0; w < 7; w++) {
            const float2 v = lds64f(rb + w * 1152);
            acc.x += v.x;
            acc.y += v.y;
        }
    }
    return acc;
}

struct Params {
    const __nv_bfloat16 *w1, *b1, *w2, *b2;
    __nv_bfloat16* out;
    alignas(64) CUtensorMap map_wo, map_w1, map_w2;
};

__global__ void __launch_bounds__(NTHREADS, 1)
fused_decode_kernel(const __nv_bfloat16* const wq, const __nv_bfloat16* const xin, const char* const kc, const char* const vc,
                    Exchange* const gx, const __grid_constant__ Params p) {
    extern __shared__ __align__(1024) unsigned char smem[];
    const uint32_t sb = (uint32_t)__cvta_generic_to_shared(smem);
    const int tid = threadIdx.x, warp = tid >> 5, lane = tid & 31;
    const int c = blockIdx.x;
    const char* kbase = kc + (size_t)c * (SK * DH * 2);
    const char* vbase = vc + (size_t)c * (SK * DH * 2);

    const int rot = (c * ROT) & (NCH - 1);
    const bool is_f1 = !(c & 1);
    const int fi = c >> 1;

    asm volatile("{\n.reg .pred p;\n.reg .b32 w;\n.reg .b64 a;\nmov.u32 w, %%ctaid.x;\nmad.wide.u32 a, w, 28672, %0;\n"
                 "setp.eq.u32 p, %1, 128;\n@p cp.async.bulk.prefetch.L2.global [a], 28672;\n}"
                 ::"l"(wq), "r"(tid) : "memory");
    uint64_t pol = 0;
    if (tid == 128) {
        mbar_init(sb + BAR_FULL, 1);
        asm volatile("fence.mbarrier_init.release.cluster;" ::: "memory");
        asm volatile("createpolicy.fractional.L2::evict_first.b64 %0, 1.0;" : "=l"(pol));
        mbar_expect_tx(sb + BAR_FULL, CHUNK);
        bulk_load(sb + SM_RING, kbase + rot * CHUNK, CHUNK, sb + BAR_FULL, pol);
    }
    if (warp == 4) {
        if (lane == 0) {
#pragma unroll
            for (int s = 0; s < NS; s++) {
                if (s) mbar_init(sb + BAR_FULL + 8 * s, 1);
                mbar_init(sb + BAR_EMPTY + 8 * s, 4);
            }
#pragma unroll
            for (int w = 0; w < 8; w++) {
                if (w < 4) mbar_init(sb + BAR_WO + 8 * w, 1);
                mbar_init(sb + BAR_W1 + 8 * w, 1);
            }
            mbar_init(sb + BAR_DRY, 4);
            mbar_init(sb + BAR_WQ, 128);
            mbar_init(sb + BAR_Q, 1);
            mbar_init(sb + BAR_E1, 1);
            mbar_init(sb + BAR_X, 1);
            mbar_init(sb + BAR_X + 8, 1);
            ctl_store(sb + SM_PROG, 0);
            ctl_store(sb + SM_DEPTH, 2);
            asm volatile("fence.mbarrier_init.release.cluster;" ::: "memory");
        }
        __syncwarp();
        asm volatile("bar.arrive 0, %0;" ::"n"(NTHREADS) : "memory");
        if (lane == 0) {
            spin_or(K1_DELAY, sb + BAR_WQ);
            int s = 1, sl = 0, landed = 0;
            uint32_t ph = 1, phl = 0;
#pragma unroll 1
            for (int i = 1; i <= 2 * NCH; i++) {
                const char* src = (i < NCH ? kbase : vbase) + ((i + rot) & (NCH - 1)) * CHUNK;
                for (int it = 0; landed < (i < 2 * NCH ? i + 1 - (int)ctl_load(sb + SM_DEPTH) : i); it++) {
                    if (mbar_test(sb + BAR_FULL + 8 * sl, phl) || it >= 4 * SPIN_LIMIT) {
                        asm volatile("red.relaxed.gpu.global.add.u32 [%0], 1;" ::"l"(gx->count + 32) : "memory");
                        ctl_store(sb + SM_PROG, ++landed);
                        if (++sl == NS) { sl = 0; phl ^= 1; }
                    } else {
                        __nanosleep(20);
                    }
                }
                if (i == 2 * NCH) break;
                mbar_wait(sb + BAR_EMPTY + 8 * s, ph);
                mbar_expect_tx(sb + BAR_FULL + 8 * s, CHUNK);
                bulk_load(sb + SM_RING + s * CHUNK, src, CHUNK, sb + BAR_FULL + 8 * s, pol);
                if (++s == NS) { s = 0; ph ^= 1; }
            }
        }
    } else if (warp < 4) {
        const int g = lane >> 2, t = lane & 3, r = lane & 7, mi = lane >> 3;
        {
            uint32_t* slot = gx->q + c * 128 + tid;
            uint32_t w = 0;
            xld32(w, slot, 0);
            const int row = tid >> 2, ch = tid & 3;
            const uint32_t dst = sb + SM_WQ + row * 64 + ((ch ^ ((row >> 1) & 3)) << 4);
            const __nv_bfloat16* src = wq + row * (NH * DH) + c * 32 + ch * 8;
#pragma unroll
            for (int i = 0; i < 14; i++)
                asm volatile("cp.async.cg.shared.global [%0], [%1], 16;" ::"r"(dst + i * 2048), "l"(src + i * 32 * (NH * DH)) : "memory");
            bar_sync(0, NTHREADS);
            asm volatile("cp.async.mbarrier.arrive.noinc.shared::cta.b64 [%0];" ::"r"(sb + BAR_WQ) : "memory");
            bar_sync(3, 256);
            w = poll32(slot, w, 0);
            xst32(slot, 0);
            sts32(sb + SM_Q + tid * 4, ~w);
        }
        bar_sync(1, 128);
        asm volatile("fence.proxy.async.shared::cta;" ::: "memory");
        if (tid == 0) mbar_arrive(sb + BAR_Q);
        int s = 0;
        uint32_t ph = 0;
        float rmax = -INFINITY;
        {
            uint32_t qf[32];
#pragma unroll
            for (int i = 0; i < 32; i++) qf[i] = lds32(sb + SM_Q + ((i ^ g) * 4 + t) * 4);
            uint32_t off[4];
#pragma unroll
            for (int i = 0; i < 4; i++)
                off[i] = sb + SM_RING + (warp * 16 + (mi & 1) * 8 + r) * 512 + (((2 * i + (mi >> 1)) ^ r) << 4);
            const bool owner = t == (g >> 1);
            uint32_t pdst = sb + SM_P + (t * 16 + warp * 4 + (g & 1)) * 2;
#pragma unroll 1
            for (int i = 0; i < NCH; i++) {
                mbar_wait(sb + BAR_FULL + 8 * s, ph);
                float acc[4][4] = {};
#pragma unroll
                for (int ks = 0; ks < 16; ks++) {
                    uint32_t a[4];
                    ldsm4(a, off[ks & 3] + s * CHUNK + (ks >> 2) * 128);
                    mma(acc[ks & 3], a, qf[2 * ks], qf[2 * ks + 1]);
                }
                __syncwarp();
                if (lane == 0) mbar_arrive(sb + BAR_EMPTY + 8 * s);
                float v[4];
#pragma unroll
                for (int e = 0; e < 4; e++) v[e] = (acc[0][e] + acc[1][e]) + (acc[2][e] + acc[3][e]);
                const float lo = (g & 1) ? v[1] : v[0], hi = (g & 1) ? v[3] : v[2];
                const uint32_t sc = pack_bf(bf_round(lo) * 0.0625f, bf_round(hi) * 0.0625f);
                if (owner) {
                    sts16(pdst, sc & 0xffffu);
                    sts16(pdst + 4, sc >> 16);
                    rmax = fmaxf(rmax, fmaxf(bf_lo(sc), bf_hi(sc)));
                }
                pdst += 128;
                if (++s == NS) { s = 0; ph ^= 1; }
            }
        }
        {
#pragma unroll
            for (int o = 16; o; o >>= 1) rmax = fmaxf(rmax, __shfl_xor_sync(0xffffffffu, rmax, o));
            if (lane == 0) sts32f(sb + SM_STAT + warp * 4, rmax);
            bar_sync(1, 128);
            const uint4 mx = lds128(sb + SM_STAT);
            const float m = fmaxf(fmaxf(__uint_as_float(mx.x), __uint_as_float(mx.y)),
                                  fmaxf(__uint_as_float(mx.z), __uint_as_float(mx.w)));
            float e[32];
            float sum = 0.f;
#pragma unroll
            for (int i = 0; i < 4; i++) {
                const uint4 w = lds128(sb + SM_P + (i * 128 + tid) * 16);
                const uint32_t ww[4] = {w.x, w.y, w.z, w.w};
#pragma unroll
                for (int j = 0; j < 4; j++) {
                    e[i * 8 + 2 * j] = __expf(bf_lo(ww[j]) - m);
                    e[i * 8 + 2 * j + 1] = __expf(bf_hi(ww[j]) - m);
                    sum += e[i * 8 + 2 * j] + e[i * 8 + 2 * j + 1];
                }
            }
#pragma unroll
            for (int o = 16; o; o >>= 1) sum += __shfl_xor_sync(0xffffffffu, sum, o);
            if (lane == 0) sts32f(sb + SM_STAT + 16 + warp * 4, sum);
            bar_sync(1, 128);
            const uint4 sm = lds128(sb + SM_STAT + 16);
            const float inv = 1.f / ((__uint_as_float(sm.x) + __uint_as_float(sm.y)) +
                                     (__uint_as_float(sm.z) + __uint_as_float(sm.w)));
#pragma unroll
            for (int i = 0; i < 4; i++) {
                uint4 w;
                w.x = pack_bf(e[i * 8 + 0] * inv, e[i * 8 + 1] * inv);
                w.y = pack_bf(e[i * 8 + 2] * inv, e[i * 8 + 3] * inv);
                w.z = pack_bf(e[i * 8 + 4] * inv, e[i * 8 + 5] * inv);
                w.w = pack_bf(e[i * 8 + 6] * inv, e[i * 8 + 7] * inv);
                sts128(sb + SM_P + (i * 128 + tid) * 16, w);
            }
            bar_sync(1, 128);
        }
        {
            uint32_t off[4];
#pragma unroll
            for (int i = 0; i < 4; i++)
                off[i] = sb + SM_RING + ((mi >> 1) * 8 + r) * 512 + warp * 128 + (((2 * i + (mi & 1)) ^ r) << 4);
            const uint32_t pmask = t == (g >> 1) ? ((g & 1) ? 0xffff0000u : 0x0000ffffu) : 0u;
            uint32_t* odst = gx->o + ((c & 15) * 8 + (c >> 4)) * 128 + (warp * 2 + (t >> 1)) * 16 + (g >> 1) * 4 +
                             (t & 1) * 2 + (g & 1);
            uint32_t lane2;
            asm volatile("mov.u32 %0, %%laneid;" : "=r"(lane2));
#pragma unroll 1
            for (int pass = 0; pass < 2; pass++) {
                int n = pass * NCH;
                asm volatile("" : "+r"(n));
                float acc[4][4] = {};
                uint32_t psrc = sb + SM_P + t * 32;
                uint32_t va[8][4], vb[8][4] = {};
                uint32_t pt[4] = {};
                uint32_t cur[4];
#pragma unroll
                for (int j = 0; j < 4; j++) cur[j] = off[j] + s * CHUNK;
                uint32_t bar = sb + BAR_FULL + 8 * s, ready = 0;
#pragma unroll 1
                for (int i = n; i > 0; i--) {
                    if (!ready) mbar_wait(bar, ph);
                    const bool wrap = bar == sb + BAR_FULL + 8 * (NS - 1);
                    const uint32_t barn = wrap ? sb + BAR_FULL : bar + 8;
                    ph ^= wrap;
                    const uint4 p0 = lds128(psrc), p1 = lds128(psrc + 16);
#pragma unroll
                    for (int j = 0; j < 2; j++) ldsm4t(va[j], cur[j & 3] + (j >> 2) * 8192);
                    uint32_t tok;
                    asm volatile("{\n.reg .pred p;\nmbarrier.test_wait.parity.shared::cta.b64 p, [%2], %3;\n"
                                 "selp.u32 %0, 1, 0, p;\nselp.u32 %1, %4, %5, p;\n}"
                                 : "=r"(ready), "=r"(tok) : "r"(barn), "r"(ph), "r"(lane), "r"(lane2) : "memory");
#pragma unroll
                    for (int j = 2; j < 8; j++) ldsm4t(va[j], cur[j & 3] + (j >> 2) * 8192);
#pragma unroll
                    for (int j = 0; j < 8; j++) mma(acc[j & 3], vb[j], pt[(j >> 2) * 2], pt[(j >> 2) * 2 + 1]);
#pragma unroll
                    for (int j = 0; j < 8; j++) ldsm4t(vb[j], cur[j & 3] + (2 + (j >> 2)) * 8192);
                    asm volatile("{\n.reg .pred p;\nsetp.eq.u32 p, %1, 0;\n@p mbarrier.arrive.shared::cta.b64 _, [%0];\n}"
                                 ::"r"(bar + 8 * NS), "r"(tok) : "memory");
                    mma(acc[0], va[0], p0.x & pmask, p0.y & pmask);
                    mma(acc[1], va[1], p0.x & pmask, p0.y & pmask);
                    mma(acc[2], va[2], p0.x & pmask, p0.y & pmask);
                    mma(acc[3], va[3], p0.x & pmask, p0.y & pmask);
                    mma(acc[0], va[4], p0.z & pmask, p0.w & pmask);
                    mma(acc[1], va[5], p0.z & pmask, p0.w & pmask);
                    mma(acc[2], va[6], p0.z & pmask, p0.w & pmask);
                    mma(acc[3], va[7], p0.z & pmask, p0.w & pmask);
                    pt[0] = p1.x & pmask;
                    pt[1] = p1.y & pmask;
                    pt[2] = p1.z & pmask;
                    pt[3] = p1.w & pmask;
                    psrc += 128;
                    bar = barn;
                    const uint32_t step = wrap ? -(NS - 1) * CHUNK : CHUNK;
#pragma unroll
                    for (int j = 0; j < 4; j++) cur[j] += step;
                }
#pragma unroll
                for (int j = 0; j < 8; j++) mma(acc[j & 3], vb[j], pt[(j >> 2) * 2], pt[(j >> 2) * 2 + 1]);
                float ev[4], od[4];
#pragma unroll
                for (int T = 0; T < 4; T++) {
                    ev[T] = acc[T][0] + acc[T][3];
                    od[T] = acc[T][1] + acc[T][2];
                }
                ev[0] += __shfl_xor_sync(0xffffffffu, ev[1], 1);
                od[0] += __shfl_xor_sync(0xffffffffu, od[1], 1);
                ev[2] += __shfl_xor_sync(0xffffffffu, ev[3], 1);
                od[2] += __shfl_xor_sync(0xffffffffu, od[3], 1);
                ev[0] += __shfl_xor_sync(0xffffffffu, ev[2], 2);
                od[0] += __shfl_xor_sync(0xffffffffu, od[2], 2);
                const float other = __shfl_xor_sync(0xffffffffu, (g & 1) ? ev[0] : od[0], 4);
                const uint32_t w = (g & 1) ? pack_bf(other, od[0]) : pack_bf(ev[0], other);
                xst32(odst, n ? w : EMPTY);
                __syncwarp();
                if (!n && lane == 0) mbar_arrive(sb + BAR_DRY);
                if (c < 112) {
                    bar_sync(1, 128);
                    if (tid == 0) {
                        const uint32_t on = n ? 0xffffffffu : 0u;
                        mbar_wait(sb + BAR_W0, ~on & 1);
                        l2_prefetch(p.w1 + c * 7168, 14336, on);
                        spin((is_f1 ? W1_DELAY : PF_DELAY) & on);
                        if (!is_f1) {
                            l2_prefetch(p.w2 + fi * 14336, 28672, on);
                            mbar_wait(sb + BAR_E1, ~on & 1);
                            spin(W2_DELAY & on);
                        }
                        tile_loads(sb + (n ? SM_WX : SM_WO + 8192), is_f1 ? &p.map_w1 : &p.map_w2,
                                   is_f1 ? fi * 32 : (fi % 28) * 16, n ? 0 : 1 << 20, is_f1 ? 64 : 224, is_f1 ? 4096 : 7168,
                                   sb + (n ? BAR_W1 : BAR_X), n ? 8 - is_f1 : 1);
                    }
                }
            }
        }
    } else {
        const int ew = warp - 5, et = tid - 160;
        const int r = lane & 7, mi = lane >> 3;
        {
            uint32_t w[7];
#pragma unroll
            for (int i = 0; i < 7; i++)
                asm volatile("ld.global.nc.u32 %0, [%1];" : "=r"(w[i]) : "l"((const uint32_t*)xin + ew * 224 + i * 32 + lane));
            bar_sync(0, NTHREADS);
            layernorm_row(w, sb + SM_XN + ew * 912, lane);
            mbar_wait(sb + BAR_WQ, 0);
            uint32_t a[8][4];
            frags_w448(a, sb + SM_WQ, ew, lane);
            const float2 q = gemv448(a, sb, ew, lane, et);
            if (et < 128) {
                xst32(gx->q + ((et >> 4) * 16 + (c >> 3)) * 128 + (c & 7) * 16 + (et & 15), ~pack_bf(q.x, q.y));
                asm volatile("bar.arrive 3, 256;" ::: "memory");
            }
        }
        const int hh = c / 7, jj = c - hh * 7;
        const int cg = fi % 28, half = fi / 28;
        const int ht0 = (c - 112) * 7 + min(ew, 6);
        uint32_t side;
        asm volatile("ld.global.nc.u32 %0, [%1];" : "=r"(side)
                     : "l"(c < 112 ? (is_f1 ? p.b1 + fi * 32 + (et & 15) * 2 : p.b2 + cg * 16 + r * 2)
                           : xin + ((ht0 & 6) + (mi & 1)) * DM + (ht0 >> 3) * 32 + (r & 3) * 8 + (ht0 & 1) * 4 + (r >> 2) * 2));
        uint32_t seen_prog = 0;
#pragma unroll 1
        for (int pass = 0; pass < 2; pass++) {
            uint32_t live = pass;
            asm volatile("" : "+r"(live));
            const uint32_t want = 0u - live, wipe = ~want;
            const int et = pin(tid - 160), ew = et >> 5, lane = et & 31;
            const int g = lane >> 2, t = lane & 3, r = lane & 7, mi = lane >> 3;
            if (et == 0) {
                if (!live) mbar_wait(sb + BAR_Q, 0);
#pragma unroll 1
                for (int it = 0; it < SPIN_LIMIT; it++) {
                    const uint32_t prog = ctl_load(sb + SM_PROG);
                    int total = 0;
                    if (prog == seen_prog) __nanosleep(100);
                    if (prog != seen_prog || prog >= 2 * NCH - 8)
                        asm volatile("ld.relaxed.gpu.global.u32 %0, [%1];" : "=r"(total) : "l"(gx->count + 32) : "memory");
                    if (total >= ALL_CHUNKS - LIFT_LEFT) {
                        ctl_store(sb + SM_DEPTH, NS);
                    } else if (prog != seen_prog) {
                        const int lead = prog * NCTA - total;
                        ctl_store(sb + SM_DEPTH, lead >= LEAD1 ? 1 : lead >= LEAD2 ? 2 : lead >= LEAD2 - 128 ? 3 : lead >= LEAD2 - 256 ? 4 : NS);
                    }
                    seen_prog = prog;
                    if (live ? total >= ALL_CHUNKS - (c < 112 ? TRIG_LEFT : 0) : mbar_test(sb + BAR_DRY, 0)) break;
                }
                tile_loads(sb + SM_WO, &p.map_wo, jj * 64, live ? hh * 256 : 1 << 20, 64, 8192, sb + (live ? BAR_WO : BAR_X + 8),
                           c >= 112 ? 0 : live ? 4 : 1);
            } else if (et == 32 && live) {
                uint32_t seen;
                mbar_wait(sb + BAR_DRY, 0);
                asm volatile("atom.release.gpu.global.add.u32 %0, [%1], 1;" : "=r"(seen) : "l"(gx->count) : "memory");
                int it = 0;
                for (seen++; seen < NCTA && ++it < SPIN_LIMIT;) {
                    __nanosleep(512);
                    asm volatile("ld.relaxed.gpu.global.u32 %0, [%1];" : "=r"(seen) : "l"(gx->count) : "memory");
                }
                asm volatile("ld.acquire.gpu.global.u32 %0, [%1];" : "=r"(seen) : "l"(gx->count) : "memory");
            }
            __syncwarp();
            bar_sync(2, 256);
            if (c >= 112) {
                if (ew < 7) {
                    const bool odd = mi & 1;
                    const int ht = (c - 112) * 7 + ew;
                    float a0, a1;
                    uint32_t* const dst = gx->h + pin((((mi >> 1) * 14 + (ht >> 3)) * 8 + (ht & 6) + (mi & 1)) * 16 + (ht & 1) * 8 + r);
                    Poll<4, 128> in(gx->part + pin(ht * 512 + lane * 4), want, want);
                    spin(R_DELAY & want);
                    in.finish([&] {
                        const uint4 (&v)[4] = in.v;
                        const float f0 = (__uint_as_float(v[0].x) + __uint_as_float(v[1].x)) + (__uint_as_float(v[2].x) + __uint_as_float(v[3].x));
                        const float f1 = (__uint_as_float(v[0].y) + __uint_as_float(v[1].y)) + (__uint_as_float(v[2].y) + __uint_as_float(v[3].y));
                        const float f2 = (__uint_as_float(v[0].z) + __uint_as_float(v[1].z)) + (__uint_as_float(v[2].z) + __uint_as_float(v[3].z));
                        const float f3 = (__uint_as_float(v[0].w) + __uint_as_float(v[1].w)) + (__uint_as_float(v[2].w) + __uint_as_float(v[3].w));
                        a0 = (odd ? f1 : f0) + __shfl_xor_sync(0xffffffffu, odd ? f0 : f1, 8);
                        a1 = (odd ? f3 : f2) + __shfl_xor_sync(0xffffffffu, odd ? f2 : f3, 8);
                    });
                    a0 += __shfl_xor_sync(0xffffffffu, a0, 16);
                    a1 += __shfl_xor_sync(0xffffffffu, a1, 16);
                    xst32(dst, bf2_add(side, pack_bf(a0, a1)) | wipe);
                }
                if (!live) bar_sync(5, 256);
                continue;
            }
            {
                const uint32_t fa = pin(sb + SM_WO + ((ew >> 1) * 64 + (mi >> 1) * 8 + r) * 128 + ((((ew & 1) * 4 + (mi & 1)) ^ r) << 4));
                const uint32_t wb = pin(sb + SM_RED + ((ew >> 1) * 544 + t * 136 + (ew & 1) * 64 + g * 2) * 4);
                const uint32_t rb = pin(sb + SM_RED + ((ew & 3) * 136 + ((ew >> 2) * 32 + (r >> 1) * 8 + mi * 2 + (r & 1)) * 2) * 4);
                uint32_t* const pdst = gx->part + pin((((jj * 8 + ew) * 2 + (lane >> 4)) * 16 + hh) * 32 + (lane & 15) * 2);
                Poll<2, 16> in(gx->o + pin((hh * 8 + g) * 128 + (ew >> 1) * 32 + t * 4), want, want);
                spin_or(O_DELAY & want, sb + BAR_WO + 8 * (ew >> 1));
                in.until(sb + BAR_WO + 8 * (ew >> 1));
                uint32_t a[8][4];
#pragma unroll
                for (int i = 0; i < 4; i++) {
                    const int ks = (i >> 1) + (i & 1) * 2;
                    ldsm4t(a[ks * 2], fa + ks * 2048);
                    ldsm4t(a[ks * 2 + 1], (fa ^ 32) + ks * 2048);
                }
                float acc[2][2][4];
                in.finish([&] {
#pragma unroll
                    for (int i = 0; i < 2; i++) {
                        mma0(acc[i][0], a[i * 4], in.v[i].x, in.v[i].y);
                        mma0(acc[i][1], a[i * 4 + 1], in.v[i].x, in.v[i].y);
                    }
#pragma unroll
                    for (int mt = 0; mt < 2; mt++) {
                        mma(acc[0][mt], a[2 + mt], in.v[0].z, in.v[0].w);
                        mma(acc[1][mt], a[6 + mt], in.v[1].z, in.v[1].w);
                    }
                });
#pragma unroll
                for (int mt = 0; mt < 2; mt++) {
                    sts64f(wb + mt * 128, acc[0][mt][0] + acc[1][mt][0], acc[0][mt][1] + acc[1][mt][1]);
                    sts64f(wb + mt * 128 + 64, acc[0][mt][2] + acc[1][mt][2], acc[0][mt][3] + acc[1][mt][3]);
                }
                bar_sync(2, 256);
                float2 v[4];
#pragma unroll
                for (int w = 0; w < 4; w++) v[w] = lds64f(rb + w * 2176);
                const float s0 = (v[0].x + v[1].x) + (v[2].x + v[3].x);
                const float s1 = (v[0].y + v[1].y) + (v[2].y + v[3].y);
                xst64(pdst, __float_as_uint(s0) | wipe, __float_as_uint(s1) | wipe);
            }
            if (et == 0 && live) mbar_arrive(sb + BAR_E1);
            const uint32_t wbar = sb + BAR_W1 + 8 * ew;
            if (is_f1) {
                constexpr uint32_t ONES = 0x3f803f80u;
                if (ew < 7) {
                    const int b = (et >> 4) & 7, pr = et & 15;
                    const uint32_t fa = pin(sb + SM_WX + (ew * 64 + (mi >> 1) * 8 + r) * 64 + (((mi & 1) ^ (r >> 1)) << 4));
                    const uint32_t wb = pin(sb + SM_RED + (ew * 288 + t * 72 + g) * 4);
                    const uint32_t sw = pin(sb + SM_RED + (ew * 288 + g * 36 + (t == (g >> 1) ? 32 : 34)) * 4);
                    const uint32_t rs = pin(sb + SM_RED + b * 144 + 128), rz = pin(sb + SM_RED + b * 144 + pr * 8);
                    const uint32_t cw = pin(sb + SM_XN + (ew * 32 + g + (t >> 1) * 16 + (t & 1) * 8) * 4), cr = pin(sb + SM_XN + pr * 8);
                    const bool odd = pin(g & 1);
                    uint32_t* const dst = gx->r + pin((((b >> 2) * 56 + fi) * 4 + (b & 3)) * 16 + (pr & 3) * 4 + (pr >> 2));
                    Poll<2, 128> in(gx->h + pin(((fi & 1) * 14 + ew * 2) * 128 + lane * 4), want, want);
                    mbar_wait(wbar, wipe & 1);
                    uint32_t a[8][4];
#pragma unroll
                    for (int ks = 0; ks < 4; ks++) {
                        ldsm4t(a[ks * 2], fa + ks * 1024);
                        ldsm4t(a[ks * 2 + 1], (fa ^ 32) + ks * 1024);
                    }
                    float cs[2][4] = {}, z[2][2][4], st[2][4];
#pragma unroll
                    for (int ks = 0; ks < 4; ks++) {
                        mma(cs[0], a[ks * 2], ONES, ONES);
                        mma(cs[1], a[ks * 2 + 1], ONES, ONES);
                    }
                    sts32f(cw, (t & 1) ? ((t & 2) ? cs[1][2] : cs[0][2]) : ((t & 2) ? cs[1][0] : cs[0][0]));
                    bar_sync(4, 224);
                    float2 cv[7];
#pragma unroll
                    for (int w = 0; w < 7; w++) cv[w] = lds64f(cr + w * 128);
                    const float cs0 = ((cv[0].x + cv[1].x) + (cv[2].x + cv[3].x)) + ((cv[4].x + cv[5].x) + cv[6].x);
                    const float cs1 = ((cv[0].y + cv[1].y) + (cv[2].y + cv[3].y)) + ((cv[4].y + cv[5].y) + cv[6].y);
                    in.finish([&] {
#pragma unroll
                        for (int i = 0; i < 2; i++) {
                            const uint32_t sa[4] = {in.v[i].x, ONES, in.v[i].y, ONES};
                            mma0(z[i][0], a[i * 4], in.v[i].x, in.v[i].y);
                            mma0(z[i][1], a[i * 4 + 1], in.v[i].x, in.v[i].y);
                            mma0(st[i], sa, in.v[i].x, in.v[i].y);
                        }
                    });
#pragma unroll
                    for (int i = 0; i < 2; i++) mma(z[i][0], a[i * 4 + 2], in.v[i].z, in.v[i].w);
#pragma unroll
                    for (int i = 0; i < 2; i++) mma(z[i][1], a[i * 4 + 3], in.v[i].z, in.v[i].w);
#pragma unroll
                    for (int i = 0; i < 2; i++) {
                        const uint32_t sa[4] = {in.v[i].z, ONES, in.v[i].w, ONES};
                        mma(st[i], sa, in.v[i].z, in.v[i].w);
                    }
#pragma unroll
                    for (int mt = 0; mt < 2; mt++) {
                        sts32f(wb + mt * 64, z[0][mt][0] + z[1][mt][0]);
                        sts32f(wb + mt * 64 + 144, z[0][mt][1] + z[1][mt][1]);
                        sts32f(wb + mt * 64 + 32, z[0][mt][2] + z[1][mt][2]);
                        sts32f(wb + mt * 64 + 176, z[0][mt][3] + z[1][mt][3]);
                    }
                    sts64f(sw, odd ? st[0][3] + st[1][3] : st[0][2] + st[1][2], odd ? st[0][1] + st[1][1] : st[0][0] + st[1][0]);
                    bar_sync(4, 224);
                    if (ew < 4) {
                        float2 sv[7], zv[7];
#pragma unroll
                        for (int w = 0; w < 7; w++) sv[w] = lds64f(rs + w * 1152);
#pragma unroll
                        for (int w = 0; w < 7; w++) zv[w] = lds64f(rz + w * 1152);
                        const float mu = (((sv[0].x + sv[1].x) + (sv[2].x + sv[3].x)) + ((sv[4].x + sv[5].x) + sv[6].x)) * (1.f / DM);
                        const float sq = ((sv[0].y + sv[1].y) + (sv[2].y + sv[3].y)) + ((sv[4].y + sv[5].y) + sv[6].y);
                        const float inv = inv_std(bf_round(fmaxf(fmaf(sq, 1.f / DM, -mu * mu), 0.f)));
                        const float mean = bf_round(mu);
                        const float z0 = ((zv[0].x + zv[1].x) + (zv[2].x + zv[3].x)) + ((zv[4].x + zv[5].x) + zv[6].x);
                        const float z1 = ((zv[0].y + zv[1].y) + (zv[2].y + zv[3].y)) + ((zv[4].y + zv[5].y) + zv[6].y);
                        const uint32_t u = pack_bf(fmaf(-mean, cs0, z0) * inv, fmaf(-mean, cs1, z1) * inv);
                        xst32(dst, bf2_relu_sq(bf2_add(u, side)) | wipe);
                    }
                    if (c == 0 && et == 128 && live) {
                        xst32(gx->count, 0);
                        xst32(gx->count + 32, 0);
                    }
                }
            } else {
                const uint32_t fa = pin(sb + SM_WX + (ew * 224 + (mi >> 1) * 8 + r) * 32 + (((mi & 1) ^ (r >> 2)) << 4));
                const uint32_t wb = pin(sb + SM_XN + (ew * 160 + (t & 1) * 80 + (g >> 1) * 4 + (t >> 1) * 2 + (g & 1)) * 4);
                const uint32_t rb = pin(sb + SM_XN + (mi * 40 + r * 4) * 4);
                const bool upper = pin(t >> 1), first = pin(ew == 0);
                uint32_t* const dst = (live ? (uint32_t*)p.out : gx->sink) + pin((half * 4 + mi) * 224 + cg * 8 + r);
                Poll<4, 128, true> in(gx->r + pin((half * 56 + ew * 7) * 64 + lane * 4), want, lane < 16 ? want : 0u,
                                      gx->h + pin((((fi & 1) * 14 + (cg >> 1)) * 8 + half * 4 + mi) * 16 + (r & 3) * 4 +
                                                  (cg & 1) * 2 + (r >> 2)),
                                      ew == 0 ? want : 0u);
                mbar_wait(wbar, wipe & 1);
                uint32_t a[14][4];
#pragma unroll
                for (int ks = 0; ks < 14; ks++) ldsm4t(a[ks], fa + ks * 512);
                float acc[4][4];
                const auto step = [&](int i) {
                    mma(acc[0], a[4 * i], in.v[i].x, in.v[i].y);
                    mma(acc[1], a[4 * i + 1], in.v[i].z, in.v[i].w);
                    if (i < 3) {
                        mma(acc[2], a[4 * i + 2], in.v[i].x, in.v[i].y);
                        mma(acc[3], a[4 * i + 3], in.v[i].z, in.v[i].w);
                    }
                };
                in.finish([&] {
                    mma0(acc[0], a[0], in.v[0].x, in.v[0].y);
                    mma0(acc[1], a[1], in.v[0].z, in.v[0].w);
                    mma0(acc[2], a[2], in.v[0].x, in.v[0].y);
                    mma0(acc[3], a[3], in.v[0].z, in.v[0].w);
                    step(1);
                });
                step(2);
                step(3);
                sts32f(wb, upper ? acc[2][0] + acc[3][0] : acc[0][0] + acc[1][0]);
                sts32f(wb + 160, upper ? acc[2][1] + acc[3][1] : acc[0][1] + acc[1][1]);
                sts32f(wb + 64, upper ? acc[2][2] + acc[3][2] : acc[0][2] + acc[1][2]);
                sts32f(wb + 224, upper ? acc[2][3] + acc[3][3] : acc[0][3] + acc[1][3]);
                bar_sync(2, 256);
                if (first) {
                    float x[8], y[8];
#pragma unroll
                    for (int w = 0; w < 8; w++) {
                        const uint4 q = lds128(rb + w * 640);
                        x[w] = __uint_as_float(q.x) + __uint_as_float(q.z);
                        y[w] = __uint_as_float(q.y) + __uint_as_float(q.w);
                    }
                    const float s0 = ((x[0] + x[1]) + (x[2] + x[3])) + ((x[4] + x[5]) + (x[6] + x[7]));
                    const float s1 = ((y[0] + y[1]) + (y[2] + y[3])) + ((y[4] + y[5]) + (y[6] + y[7]));
                    *dst = bf2_add(in.word, bf2_add(pack_bf(s0, s1), side));
                }
                exit_if(live);
            }
            if (!live) bar_sync(5, 256);
        }
    }
}

using EncodeFn = CUresult (*)(CUtensorMap*, CUtensorMapDataType, cuuint32_t, void*, const cuuint64_t*, const cuuint64_t*,
                              const cuuint32_t*, const cuuint32_t*, CUtensorMapInterleave, CUtensorMapSwizzle,
                              CUtensorMapL2promotion, CUtensorMapFloatOOBfill);

void encode_map(EncodeFn fn, CUtensorMap* map, const void* base, int rows, int cols, int box_rows, int box_cols,
                CUtensorMapSwizzle swizzle) {
    const cuuint64_t dims[2] = {(cuuint64_t)cols, (cuuint64_t)rows};
    const cuuint64_t strides[1] = {(cuuint64_t)cols * 2};
    const cuuint32_t box[2] = {(cuuint32_t)box_cols, (cuuint32_t)box_rows};
    const cuuint32_t steps[2] = {1, 1};
    fn(map, CU_TENSOR_MAP_DATA_TYPE_BFLOAT16, 2, const_cast<void*>(base), dims, strides, box, steps,
       CU_TENSOR_MAP_INTERLEAVE_NONE, swizzle, CU_TENSOR_MAP_L2_PROMOTION_L2_128B, CU_TENSOR_MAP_FLOAT_OOB_FILL_NONE);
}

}

extern "C" void kernel_launch(void* const* d_in, const int* in_sizes, int n_in, void* d_out, int out_size) {
    (void)in_sizes; (void)n_in; (void)out_size;
    Params p;
    p.w1 = (const __nv_bfloat16*)d_in[6];
    p.b1 = (const __nv_bfloat16*)d_in[7];
    p.w2 = (const __nv_bfloat16*)d_in[8];
    p.b2 = (const __nv_bfloat16*)d_in[9];
    p.out = (__nv_bfloat16*)d_out;
    Exchange* xch = nullptr;
    cudaGetSymbolAddress((void**)&xch, g_x);
    void* fn = nullptr;
    cudaDriverEntryPointQueryResult found;
    cudaGetDriverEntryPoint("cuTensorMapEncodeTiled", &fn, cudaEnableDefault, &found);
    encode_map((EncodeFn)fn, &p.map_wo, d_in[4], NH * DH, DM, 64, 64, CU_TENSOR_MAP_SWIZZLE_128B);
    encode_map((EncodeFn)fn, &p.map_w1, p.w1, DM, FF, 64, 32, CU_TENSOR_MAP_SWIZZLE_64B);
    encode_map((EncodeFn)fn, &p.map_w2, p.w2, FF, DM, 224, 16, CU_TENSOR_MAP_SWIZZLE_32B);
    cudaFuncSetAttribute(fused_decode_kernel, cudaFuncAttributeMaxDynamicSharedMemorySize, SM_TOTAL);
    fused_decode_kernel<<<NCTA, NTHREADS, SM_TOTAL>>>((const __nv_bfloat16*)d_in[3], (const __nv_bfloat16*)d_in[0],
                                                      (const char*)d_in[1], (const char*)d_in[2], xch, p);
}
```

```cpp
#include <cuda.h>
#include <cuda_runtime.h>
#include <cuda_bf16.h>
#include <stdint.h>

namespace {

constexpr int DM = 448, NH = 16, SK = 4096, DH = 256, FF = 1792;
constexpr int NCTA = 128;
constexpr int CHUNK = 32768;
constexpr int NCH = SK / 64;
constexpr int NS = 5;
constexpr int ALL_CHUNKS = NCTA * 2 * NCH;
constexpr int LEAD1 = 128;
constexpr int LEAD2 = -128;
constexpr int LIFT_LEFT = 370;
constexpr int TRIG_LEFT = 220;
constexpr int K1_DELAY = 1000;
constexpr int Q_SLEEP = 100;
constexpr int W1_DELAY = 600;
constexpr int PF_DELAY = 500;
constexpr int W2_DELAY = 600;
constexpr int ROT = 32;
constexpr int R_DELAY = 200;
constexpr int O_DELAY = 1600;
constexpr int NTHREADS = 13 * 32;
constexpr int SPIN_LIMIT = 1 << 18;
constexpr int WAIT_LIMIT = 1 << 15;

constexpr int SM_RING = 0;
constexpr int SM_WX = 0;
constexpr int SM_WQ = NS * CHUNK;
constexpr int SM_WO = SM_WQ;
constexpr int SM_P = SM_WQ + 32768;
constexpr int SM_RED = SM_P + 8192;
constexpr int SM_XN = SM_RED + 4 * 544 * 4;
constexpr int SM_Q = SM_XN + 8 * 456 * 2;
constexpr int SM_STAT = SM_Q + 512;
constexpr int SM_PROG = SM_STAT + 32, SM_DEPTH = SM_STAT + 36;
constexpr int SM_BAR = SM_STAT + 64;
constexpr int BAR_FULL = SM_BAR, BAR_EMPTY = BAR_FULL + 8 * NS, BAR_WO = BAR_EMPTY + 8 * NS, BAR_DRY = BAR_WO + 32,
              BAR_WQ = BAR_DRY + 8, BAR_Q = BAR_WQ + 8, BAR_W0 = BAR_WO + 24, BAR_E1 = BAR_Q + 8, BAR_X = BAR_E1 + 8,
              BAR_W1 = BAR_X + 16;
constexpr int SM_TOTAL = BAR_W1 + 64;
static_assert(SM_TOTAL <= 232448, "shared memory budget");

struct Exchange {
    uint32_t q[NCTA * 128];
    uint32_t o[NH * 8 * 128];
    uint32_t part[14 * 8 * 16 * 32];
    uint32_t h[2 * 14 * 8 * 16];
    uint32_t r[2 * 56 * 4 * 16];
    uint32_t count[64];
    uint32_t sink[8 * 224];
};
__device__ __align__(128) Exchange g_x;

__device__ __forceinline__ void mbar_init(uint32_t bar, uint32_t count) {
    asm volatile("mbarrier.init.shared::cta.b64 [%0], %1;" ::"r"(bar), "r"(count) : "memory");
}
__device__ __forceinline__ void mbar_arrive(uint32_t bar) {
    asm volatile("mbarrier.arrive.shared::cta.b64 _, [%0];" ::"r"(bar) : "memory");
}
__device__ __forceinline__ void mbar_expect_tx(uint32_t bar, uint32_t bytes) {
    asm volatile("mbarrier.arrive.expect_tx.shared::cta.b64 _, [%0], %1;" ::"r"(bar), "r"(bytes) : "memory");
}
__device__ __forceinline__ void mbar_wait(uint32_t bar, uint32_t parity) {
    asm volatile("{\n.reg .pred p, q;\n.reg .u32 n;\nmov.u32 n, %2;\n"
                 "RETRY:\nsub.u32 n, n, 1;\nsetp.ne.u32 q, n, 0;\n"
                 "mbarrier.try_wait.parity.shared::cta.b64 p, [%0], %1;\nand.pred q, q, !p;\n@q bra RETRY;\n}"
                 ::"r"(bar), "r"(parity), "n"(WAIT_LIMIT) : "memory");
}
__device__ __forceinline__ uint32_t mbar_test(uint32_t bar, uint32_t parity) {
    uint32_t done;
    asm volatile("{\n.reg .pred p;\nmbarrier.test_wait.parity.shared::cta.b64 p, [%1], %2;\nselp.u32 %0, 1, 0, p;\n}"
                 : "=r"(done) : "r"(bar), "r"(parity) : "memory");
    return done;
}
__device__ __forceinline__ void exit_if(uint32_t on) {
    asm volatile("{\n.reg .pred p;\nsetp.ne.u32 p, %0, 0;\n@p exit;\n}" ::"r"(on) : "memory");
}
__device__ __forceinline__ void spin(uint32_t cycles) {
    const uint32_t t0 = (uint32_t)clock();
    do {
    } while ((uint32_t)clock() - t0 < cycles);
}
__device__ __forceinline__ void spin_or(uint32_t cycles, uint32_t bar) {
    const uint32_t t0 = (uint32_t)clock();
    do {
    } while (!mbar_test(bar, 0) && (uint32_t)clock() - t0 < cycles);
}
__device__ __forceinline__ void l2_prefetch(const void* src, uint32_t bytes, uint32_t on) {
    asm volatile("{\n.reg .pred p;\nsetp.ne.u32 p, %2, 0;\n@p cp.async.bulk.prefetch.L2.global [%0], %1;\n}"
                 ::"l"(src), "r"(bytes), "r"(on) : "memory");
}
__device__ __forceinline__ void bulk_load(uint32_t dst, const void* src, uint32_t bytes, uint32_t bar, uint64_t pol) {
    asm volatile("cp.async.bulk.shared::cluster.global.mbarrier::complete_tx::bytes.L2::cache_hint [%0], [%1], %2, [%3], %4;"
                 ::"r"(dst), "l"(src), "r"(bytes), "r"(bar), "l"(pol) : "memory");
}
__device__ __forceinline__ void tile_loads(uint32_t dst, const CUtensorMap* map, int col, int row, int rows, uint32_t bytes,
                                           uint32_t bar, int n) {
#pragma unroll 1
    for (int i = 0; i < n; i++, dst += bytes, row += rows, bar += 8) {
        mbar_expect_tx(bar, bytes);
        asm volatile("cp.async.bulk.tensor.2d.shared::cluster.global.mbarrier::complete_tx::bytes [%0], [%1, {%2, %3}], [%4];"
                     ::"r"(dst), "l"(map), "r"(col), "r"(row), "r"(bar) : "memory");
    }
}
__device__ __forceinline__ void bar_sync(int id, int n) { asm volatile("bar.sync %0, %1;" ::"r"(id), "r"(n) : "memory"); }

__device__ __forceinline__ void ldsm4(uint32_t (&r)[4], uint32_t a) {
    asm volatile("ldmatrix.sync.aligned.m8n8.x4.shared.b16 {%0,%1,%2,%3}, [%4];"
                 : "=r"(r[0]), "=r"(r[1]), "=r"(r[2]), "=r"(r[3]) : "r"(a) : "memory");
}
__device__ __forceinline__ void ldsm4t(uint32_t (&r)[4], uint32_t a) {
    asm volatile("ldmatrix.sync.aligned.m8n8.x4.trans.shared.b16 {%0,%1,%2,%3}, [%4];"
                 : "=r"(r[0]), "=r"(r[1]), "=r"(r[2]), "=r"(r[3]) : "r"(a) : "memory");
}
__device__ __forceinline__ void mma(float (&c)[4], const uint32_t (&a)[4], uint32_t b0, uint32_t b1) {
    asm volatile("mma.sync.aligned.m16n8k16.row.col.f32.bf16.bf16.f32 {%0,%1,%2,%3}, {%4,%5,%6,%7}, {%8,%9}, {%0,%1,%2,%3};"
                 : "+f"(c[0]), "+f"(c[1]), "+f"(c[2]), "+f"(c[3])
                 : "r"(a[0]), "r"(a[1]), "r"(a[2]), "r"(a[3]), "r"(b0), "r"(b1));
}
__device__ __forceinline__ void mma0(float (&c)[4], const uint32_t (&a)[4], uint32_t b0, uint32_t b1) {
    asm volatile("mma.sync.aligned.m16n8k16.row.col.f32.bf16.bf16.f32 {%0,%1,%2,%3}, {%4,%5,%6,%7}, {%8,%9}, {%10,%10,%10,%10};"
                 : "=f"(c[0]), "=f"(c[1]), "=f"(c[2]), "=f"(c[3])
                 : "r"(a[0]), "r"(a[1]), "r"(a[2]), "r"(a[3]), "r"(b0), "r"(b1), "f"(0.f));
}
__device__ __forceinline__ uint32_t lds32(uint32_t a) {
    uint32_t v;
    asm volatile("ld.shared.u32 %0, [%1];" : "=r"(v) : "r"(a) : "memory");
    return v;
}
__device__ __forceinline__ uint32_t ctl_load(uint32_t a) {
    uint32_t v;
    asm volatile("ld.volatile.shared.u32 %0, [%1];" : "=r"(v) : "r"(a) : "memory");
    return v;
}
__device__ __forceinline__ void ctl_store(uint32_t a, uint32_t v) {
    asm volatile("st.volatile.shared.u32 [%0], %1;" ::"r"(a), "r"(v) : "memory");
}
__device__ __forceinline__ float2 lds64f(uint32_t a) {
    float2 v;
    asm volatile("ld.shared.v2.f32 {%0,%1}, [%2];" : "=f"(v.x), "=f"(v.y) : "r"(a) : "memory");
    return v;
}
__device__ __forceinline__ uint4 lds128(uint32_t a) {
    uint4 v;
    asm volatile("ld.shared.v4.u32 {%0,%1,%2,%3}, [%4];" : "=r"(v.x), "=r"(v.y), "=r"(v.z), "=r"(v.w) : "r"(a) : "memory");
    return v;
}
__device__ __forceinline__ void sts16(uint32_t a, uint32_t v) {
    asm volatile("st.shared.u16 [%0], %1;" ::"r"(a), "h"((unsigned short)v) : "memory");
}
__device__ __forceinline__ void sts32(uint32_t a, uint32_t v) {
    asm volatile("st.shared.u32 [%0], %1;" ::"r"(a), "r"(v) : "memory");
}
__device__ __forceinline__ void sts32f(uint32_t a, float v) {
    asm volatile("st.shared.f32 [%0], %1;" ::"r"(a), "f"(v) : "memory");
}
__device__ __forceinline__ void sts64f(uint32_t a, float x, float y) {
    asm volatile("st.shared.v2.f32 [%0], {%1,%2};" ::"r"(a), "f"(x), "f"(y) : "memory");
}
__device__ __forceinline__ void sts128(uint32_t a, uint4 v) {
    asm volatile("st.shared.v4.u32 [%0], {%1,%2,%3,%4};" ::"r"(a), "r"(v.x), "r"(v.y), "r"(v.z), "r"(v.w) : "memory");
}

constexpr uint32_t EMPTY = 0xffffffffu;
__device__ __forceinline__ void xld32(uint32_t& v, const uint32_t* p, uint32_t empty) {
    asm volatile("{\n.reg .pred p;\nsetp.eq.u32 p, %0, %2;\n@p ld.relaxed.gpu.global.u32 %0, [%1];\n}"
                 : "+r"(v) : "l"(p), "r"(empty) : "memory");
}
__device__ __forceinline__ void xld128(uint4& v, const uint32_t* p, uint32_t top) {
    asm volatile("{\n.reg .pred p;\nsetp.eq.u32 p, %5, 0xffffffff;\n@p ld.relaxed.gpu.global.v4.u32 {%0,%1,%2,%3}, [%4];\n}"
                 : "+r"(v.x), "+r"(v.y), "+r"(v.z), "+r"(v.w) : "l"(p), "r"(top) : "memory");
}
__device__ __forceinline__ void xst32(uint32_t* p, uint32_t v) {
    asm volatile("st.relaxed.gpu.global.u32 [%0], %1;" ::"l"(p), "r"(v) : "memory");
}
__device__ __forceinline__ void xst64(uint32_t* p, uint32_t a, uint32_t b) {
    asm volatile("st.relaxed.gpu.global.v2.u32 [%0], {%1,%2};" ::"l"(p), "r"(a), "r"(b) : "memory");
}
__device__ __forceinline__ uint32_t top_word(const uint4& v) { return max(__vimax3_u32(v.x, v.y, v.z), v.w); }
template <int N, int STRIDE, bool WORD = false>
struct Poll {
    uint4 v[N];
    uint32_t top[N], word, want;
    const uint32_t *src, *wsrc;
    int left;
    __device__ __forceinline__ Poll(const uint32_t* s, uint32_t init, uint32_t init_last, const uint32_t* ws = nullptr,
                                    uint32_t init_word = 0)
        : word(init_word), want(init), src(s), wsrc(ws), left(init ? SPIN_LIMIT : 2) {
#pragma unroll
        for (int i = 0; i < N; i++) {
            top[i] = i == N - 1 ? init_last : init;
            v[i] = make_uint4(top[i], top[i], top[i], top[i]);
        }
    }
    __device__ __forceinline__ void issue() {
#pragma unroll
        for (int i = 0; i < N; i++) xld128(v[i], src + i * STRIDE, top[i]);
        if (WORD) xld32(word, wsrc, EMPTY);
        left--;
    }
    __device__ __forceinline__ bool missing() {
        uint32_t m = WORD ? word : 0;
#pragma unroll
        for (int i = 0; i < N; i++) {
            top[i] = top_word(v[i]);
            m = max(m, top[i]);
        }
        return __any_sync(0xffffffffu, m == want && left > 0);
    }
    __device__ __forceinline__ void until(uint32_t bar) {
#pragma unroll 1
        while (!mbar_test(bar, 0)) {
            issue();
            if (!missing()) break;
        }
        mbar_wait(bar, ~want & 1);
    }
    template <class F>
    __device__ __forceinline__ void finish(F use) {
        bool again;
#pragma unroll 1
        do {
            issue();
            again = missing();
            use();
        } while (again);
    }
};
__device__ __forceinline__ uint32_t pin(uint32_t v) {
    asm volatile("shfl.sync.bfly.b32 %0, %0, 0, 0x1f, 0xffffffff;" : "+r"(v));
    return v;
}
__device__ __forceinline__ uint32_t bf2_add(uint32_t a, uint32_t b) {
    uint32_t r;
    asm("add.rn.bf16x2 %0, %1, %2;" : "=r"(r) : "r"(a), "r"(b));
    return r;
}
__device__ __forceinline__ uint32_t bf2_relu_sq(uint32_t a) {
    uint32_t r;
    asm("{\n.reg .b32 m;\nmax.bf16x2 m, %1, %2;\nmul.rn.bf16x2 %0, m, m;\n}" : "=r"(r) : "r"(a), "r"(0));
    return r;
}

__device__ __forceinline__ uint32_t pack_bf(float lo, float hi) {
    uint32_t r;
    asm("cvt.rn.bf16x2.f32 %0, %1, %2;" : "=r"(r) : "f"(hi), "f"(lo));
    return r;
}
__device__ __forceinline__ float bf_round(float v) { return __uint_as_float(pack_bf(0.f, v)); }
__device__ __forceinline__ float bf_lo(uint32_t w) { return __uint_as_float(w << 16); }
__device__ __forceinline__ float bf_hi(uint32_t w) { return __uint_as_float(w & 0xffff0000u); }

__device__ __forceinline__ float inv_std(float var) {
    float sd, inv;
    asm("sqrt.approx.ftz.f32 %0, %1;" : "=f"(sd) : "f"(bf_round(var + 1e-5f)));
    asm("rcp.approx.ftz.f32 %0, %1;" : "=f"(inv) : "f"(bf_round(sd)));
    return inv;
}

__device__ __forceinline__ void layernorm_row(const uint32_t (&w)[7], uint32_t dst, int lane) {
    const float shift = bf_lo(__shfl_sync(0xffffffffu, w[0], 0));
    float s = 0.f, ss = 0.f;
#pragma unroll
    for (int i = 0; i < 7; i++) {
        const float a = bf_lo(w[i]) - shift, b = bf_hi(w[i]) - shift;
        s += a + b;
        ss = fmaf(a, a, fmaf(b, b, ss));
    }
#pragma unroll
    for (int o = 16; o; o >>= 1) {
        s += __shfl_xor_sync(0xffffffffu, s, o);
        ss += __shfl_xor_sync(0xffffffffu, ss, o);
    }
    const float md = s * (1.f / DM);
    const float mean = bf_round(shift + md);
    const float inv = inv_std(bf_round(fmaxf(ss * (1.f / DM) - md * md, 0.f)));
#pragma unroll
    for (int i = 0; i < 7; i++) {
        const float a = bf_round(bf_lo(w[i]) - mean) * inv, b = bf_round(bf_hi(w[i]) - mean) * inv;
        sts32(dst + (i * 32 + lane) * 4, pack_bf(a, b));
    }
}

__device__ __forceinline__ void frags_w448(uint32_t (&a)[8][4], uint32_t src, int ew, int lane) {
    const int r = lane & 7, mi = lane >> 3;
    const uint32_t base = src + ((ew < 7 ? ew : 0) * 64 + (mi >> 1) * 8 + r) * 64;
#pragma unroll
    for (int ks = 0; ks < 4; ks++)
#pragma unroll
        for (int mt = 0; mt < 2; mt++)
            ldsm4t(a[ks * 2 + mt], base + ks * 1024 + (((2 * mt + (mi & 1)) ^ (r >> 1)) << 4));
}
__device__ __forceinline__ float2 gemv448(const uint32_t (&a)[8][4], uint32_t sb, int ew, int lane, int et) {
    const int g = lane >> 2, t = lane & 3;
    bar_sync(2, 256);
    if (ew < 7) {
        float c[4][4] = {};
        const uint32_t xb = sb + SM_XN + (g * 228 + ew * 32 + t) * 4;
#pragma unroll
        for (int ks = 0; ks < 4; ks++) {
            const uint32_t b0 = lds32(xb + ks * 32), b1 = lds32(xb + ks * 32 + 16);
            mma(c[(ks & 1) * 2], a[ks * 2], b0, b1);
            mma(c[(ks & 1) * 2 + 1], a[ks * 2 + 1], b0, b1);
        }
        const uint32_t rb = sb + SM_RED + (ew * 288 + t * 72 + g) * 4;
#pragma unroll
        for (int mt = 0; mt < 2; mt++) {
            sts32f(rb + mt * 64, c[mt][0] + c[2 + mt][0]);
            sts32f(rb + mt * 64 + 144, c[mt][1] + c[2 + mt][1]);
            sts32f(rb + mt * 64 + 32, c[mt][2] + c[2 + mt][2]);
            sts32f(rb + mt * 64 + 176, c[mt][3] + c[2 + mt][3]);
        }
    }
    bar_sync(2, 256);
    float2 acc = make_float2(0.f, 0.f);
    if (et < 128) {
        const uint32_t rb = sb + SM_RED + ((et >> 4) * 36 + (et & 15) * 2) * 4;
#pragma unroll
        for (int w = 0; w < 7; w++) {
            const float2 v = lds64f(rb + w * 1152);
            acc.x += v.x;
            acc.y += v.y;
        }
    }
    return acc;
}

struct Params {
    const __nv_bfloat16 *w1, *b1, *w2, *b2;
    __nv_bfloat16* out;
    alignas(64) CUtensorMap map_wo, map_w1, map_w2;
};

__global__ void __launch_bounds__(NTHREADS, 1)
fused_decode_kernel(const __nv_bfloat16* const wq, const __nv_bfloat16* const xin, const char* const kc, const char* const vc,
                    Exchange* const gx, const __grid_constant__ Params p) {
    extern __shared__ __align__(1024) unsigned char smem[];
    const uint32_t sb = (uint32_t)__cvta_generic_to_shared(smem);
    const int tid = threadIdx.x, warp = tid >> 5, lane = tid & 31;
    const int c = blockIdx.x;
    const char* kbase = kc + (size_t)c * (SK * DH * 2);
    const char* vbase = vc + (size_t)c * (SK * DH * 2);

    const int rot = (c * ROT) & (NCH - 1);
    const bool is_f1 = !(c & 1);
    const int fi = c >> 1;

    asm volatile("{\n.reg .pred p;\n.reg .b32 w;\n.reg .b64 a;\nmov.u32 w, %%ctaid.x;\nmad.wide.u32 a, w, 28672, %0;\n"
                 "setp.eq.u32 p, %1, 128;\n@p cp.async.bulk.prefetch.L2.global [a], 28672;\n}"
                 ::"l"(wq), "r"(tid) : "memory");
    uint64_t pol = 0;
    if (tid == 128) {
        mbar_init(sb + BAR_FULL, 1);
        asm volatile("fence.mbarrier_init.release.cluster;" ::: "memory");
        asm volatile("createpolicy.fractional.L2::evict_first.b64 %0, 1.0;" : "=l"(pol));
        mbar_expect_tx(sb + BAR_FULL, CHUNK);
        bulk_load(sb + SM_RING, kbase + rot * CHUNK, CHUNK, sb + BAR_FULL, pol);
    }
    if (warp == 4) {
        if (lane == 0) {
#pragma unroll
            for (int s = 0; s < NS; s++) {
                if (s) mbar_init(sb + BAR_FULL + 8 * s, 1);
                mbar_init(sb + BAR_EMPTY + 8 * s, 4);
            }
#pragma unroll
            for (int w = 0; w < 8; w++) {
                if (w < 4) mbar_init(sb + BAR_WO + 8 * w, 1);
                mbar_init(sb + BAR_W1 + 8 * w, 1);
            }
            mbar_init(sb + BAR_DRY, 4);
            mbar_init(sb + BAR_WQ, 128);
            mbar_init(sb + BAR_Q, 1);
            mbar_init(sb + BAR_E1, 1);
            mbar_init(sb + BAR_X, 1);
            mbar_init(sb + BAR_X + 8, 1);
            ctl_store(sb + SM_PROG, 0);
            ctl_store(sb + SM_DEPTH, 2);
            asm volatile("fence.mbarrier_init.release.cluster;" ::: "memory");
        }
        __syncwarp();
        asm volatile("bar.arrive 0, %0;" ::"n"(NTHREADS) : "memory");
        if (lane == 0) {
            spin_or(K1_DELAY, sb + BAR_WQ);
            int s = 1, sl = 0, landed = 0;
            uint32_t ph = 1, phl = 0;
#pragma unroll 1
            for (int i = 1; i <= 2 * NCH; i++) {
                const char* src = (i < NCH ? kbase : vbase) + ((i + rot) & (NCH - 1)) * CHUNK;
                for (int it = 0; landed < (i < 2 * NCH ? i + 1 - (int)ctl_load(sb + SM_DEPTH) : i); it++) {
                    if (mbar_test(sb + BAR_FULL + 8 * sl, phl) || it >= 4 * SPIN_LIMIT) {
                        asm volatile("red.relaxed.gpu.global.add.u32 [%0], 1;" ::"l"(gx->count + 32) : "memory");
                        ctl_store(sb + SM_PROG, ++landed);
                        if (++sl == NS) { sl = 0; phl ^= 1; }
                    } else {
                        __nanosleep(20);
                    }
                }
                if (i == 2 * NCH) break;
                mbar_wait(sb + BAR_EMPTY + 8 * s, ph);
                mbar_expect_tx(sb + BAR_FULL + 8 * s, CHUNK);
                bulk_load(sb + SM_RING + s * CHUNK, src, CHUNK, sb + BAR_FULL + 8 * s, pol);
                if (++s == NS) { s = 0; ph ^= 1; }
            }
        }
    } else if (warp < 4) {
        const int g = lane >> 2, t = lane & 3, r = lane & 7, mi = lane >> 3;
        {
            const int row = tid >> 2, ch = tid & 3;
            const uint32_t dst = sb + SM_WQ + row * 64 + ((ch ^ ((row >> 1) & 3)) << 4);
            const __nv_bfloat16* src = wq + row * (NH * DH) + c * 32 + ch * 8;
#pragma unroll
            for (int i = 0; i < 14; i++)
                asm volatile("cp.async.cg.shared.global [%0], [%1], 16;" ::"r"(dst + i * 2048), "l"(src + i * 32 * (NH * DH)) : "memory");
            uint32_t* slot = gx->q + c * 128 + tid;
            uint32_t w = 0;
#pragma unroll 1
            for (int it = 0; it < SPIN_LIMIT; it++) {
                xld32(w, slot, 0);
                if (it == 0) {
                    bar_sync(0, NTHREADS);
                    asm volatile("cp.async.mbarrier.arrive.noinc.shared::cta.b64 [%0];" ::"r"(sb + BAR_WQ) : "memory");
                }
                if (!__any_sync(0xffffffffu, w == 0)) break;
                __nanosleep(Q_SLEEP);
            }
            xst32(slot, 0);
            sts32(sb + SM_Q + tid * 4, ~w);
        }
        bar_sync(1, 128);
        if (tid == 0) mbar_arrive(sb + BAR_Q);
        int s = 0;
        uint32_t ph = 0;
        float rmax = -INFINITY;
        {
            uint32_t qf[32];
#pragma unroll
            for (int i = 0; i < 32; i++) qf[i] = lds32(sb + SM_Q + ((i ^ g) * 4 + t) * 4);
            uint32_t off[4];
#pragma unroll
            for (int i = 0; i < 4; i++)
                off[i] = sb + SM_RING + (warp * 16 + (mi & 1) * 8 + r) * 512 + (((2 * i + (mi >> 1)) ^ r) << 4);
            const bool owner = t == (g >> 1);
            uint32_t pdst = sb + SM_P + (t * 16 + warp * 4 + (g & 1)) * 2;
#pragma unroll 1
            for (int i = 0; i < NCH; i++) {
                mbar_wait(sb + BAR_FULL + 8 * s, ph);
                float acc[4][4] = {};
#pragma unroll
                for (int ks = 0; ks < 16; ks++) {
                    uint32_t a[4];
                    ldsm4(a, off[ks & 3] + s * CHUNK + (ks >> 2) * 128);
                    mma(acc[ks & 3], a, qf[2 * ks], qf[2 * ks + 1]);
                }
                __syncwarp();
                if (lane == 0) mbar_arrive(sb + BAR_EMPTY + 8 * s);
                float v[4];
#pragma unroll
                for (int e = 0; e < 4; e++) v[e] = (acc[0][e] + acc[1][e]) + (acc[2][e] + acc[3][e]);
                const float lo = (g & 1) ? v[1] : v[0], hi = (g & 1) ? v[3] : v[2];
                const uint32_t sc = pack_bf(bf_round(lo) * 0.0625f, bf_round(hi) * 0.0625f);
                if (owner) {
                    sts16(pdst, sc & 0xffffu);
                    sts16(pdst + 4, sc >> 16);
                    rmax = fmaxf(rmax, fmaxf(bf_lo(sc), bf_hi(sc)));
                }
                pdst += 128;
                if (++s == NS) { s = 0; ph ^= 1; }
            }
        }
        mbar_wait(sb + BAR_WQ, 0);
        asm volatile("fence.proxy.async.shared::cta;" ::: "memory");
        {
#pragma unroll
            for (int o = 16; o; o >>= 1) rmax = fmaxf(rmax, __shfl_xor_sync(0xffffffffu, rmax, o));
            if (lane == 0) sts32f(sb + SM_STAT + warp * 4, rmax);
            bar_sync(1, 128);
            const uint4 mx = lds128(sb + SM_STAT);
            const float m = fmaxf(fmaxf(__uint_as_float(mx.x), __uint_as_float(mx.y)),
                                  fmaxf(__uint_as_float(mx.z), __uint_as_float(mx.w)));
            float e[32];
            float sum = 0.f;
#pragma unroll
            for (int i = 0; i < 4; i++) {
                const uint4 w = lds128(sb + SM_P + (i * 128 + tid) * 16);
                const uint32_t ww[4] = {w.x, w.y, w.z, w.w};
#pragma unroll
                for (int j = 0; j < 4; j++) {
                    e[i * 8 + 2 * j] = __expf(bf_lo(ww[j]) - m);
                    e[i * 8 + 2 * j + 1] = __expf(bf_hi(ww[j]) - m);
                    sum += e[i * 8 + 2 * j] + e[i * 8 + 2 * j + 1];
                }
            }
#pragma unroll
            for (int o = 16; o; o >>= 1) sum += __shfl_xor_sync(0xffffffffu, sum, o);
            if (lane == 0) sts32f(sb + SM_STAT + 16 + warp * 4, sum);
            bar_sync(1, 128);
            const uint4 sm = lds128(sb + SM_STAT + 16);
            const float inv = 1.f / ((__uint_as_float(sm.x) + __uint_as_float(sm.y)) +
                                     (__uint_as_float(sm.z) + __uint_as_float(sm.w)));
#pragma unroll
            for (int i = 0; i < 4; i++) {
                uint4 w;
                w.x = pack_bf(e[i * 8 + 0] * inv, e[i * 8 + 1] * inv);
                w.y = pack_bf(e[i * 8 + 2] * inv, e[i * 8 + 3] * inv);
                w.z = pack_bf(e[i * 8 + 4] * inv, e[i * 8 + 5] * inv);
                w.w = pack_bf(e[i * 8 + 6] * inv, e[i * 8 + 7] * inv);
                sts128(sb + SM_P + (i * 128 + tid) * 16, w);
            }
            bar_sync(1, 128);
        }
        {
            uint32_t off[4];
#pragma unroll
            for (int i = 0; i < 4; i++)
                off[i] = sb + SM_RING + ((mi >> 1) * 8 + r) * 512 + warp * 128 + (((2 * i + (mi & 1)) ^ r) << 4);
            const uint32_t pmask = t == (g >> 1) ? ((g & 1) ? 0xffff0000u : 0x0000ffffu) : 0u;
            uint32_t* odst = gx->o + ((c & 15) * 8 + (c >> 4)) * 128 + (warp * 2 + (t >> 1)) * 16 + (g >> 1) * 4 +
                             (t & 1) * 2 + (g & 1);
            uint32_t lane2;
            asm volatile("mov.u32 %0, %%laneid;" : "=r"(lane2));
#pragma unroll 1
            for (int pass = 0; pass < 2; pass++) {
                int n = pass * NCH;
                asm volatile("" : "+r"(n));
                float acc[4][4] = {};
                uint32_t psrc = sb + SM_P + t * 32;
                uint32_t va[8][4], vb[8][4] = {};
                uint32_t pt[4] = {};
                uint32_t cur[4];
#pragma unroll
                for (int j = 0; j < 4; j++) cur[j] = off[j] + s * CHUNK;
                uint32_t bar = sb + BAR_FULL + 8 * s, ready = 0;
#pragma unroll 1
                for (int i = n; i > 0; i--) {
                    if (!ready) mbar_wait(bar, ph);
                    const bool wrap = bar == sb + BAR_FULL + 8 * (NS - 1);
                    const uint32_t barn = wrap ? sb + BAR_FULL : bar + 8;
                    ph ^= wrap;
                    const uint4 p0 = lds128(psrc), p1 = lds128(psrc + 16);
#pragma unroll
                    for (int j = 0; j < 2; j++) ldsm4t(va[j], cur[j & 3] + (j >> 2) * 8192);
                    uint32_t tok;
                    asm volatile("{\n.reg .pred p;\nmbarrier.test_wait.parity.shared::cta.b64 p, [%2], %3;\n"
                                 "selp.u32 %0, 1, 0, p;\nselp.u32 %1, %4, %5, p;\n}"
                                 : "=r"(ready), "=r"(tok) : "r"(barn), "r"(ph), "r"(lane), "r"(lane2) : "memory");
#pragma unroll
                    for (int j = 2; j < 8; j++) ldsm4t(va[j], cur[j & 3] + (j >> 2) * 8192);
#pragma unroll
                    for (int j = 0; j < 8; j++) mma(acc[j & 3], vb[j], pt[(j >> 2) * 2], pt[(j >> 2) * 2 + 1]);
#pragma unroll
                    for (int j = 0; j < 8; j++) ldsm4t(vb[j], cur[j & 3] + (2 + (j >> 2)) * 8192);
                    asm volatile("{\n.reg .pred p;\nsetp.eq.u32 p, %1, 0;\n@p mbarrier.arrive.shared::cta.b64 _, [%0];\n}"
                                 ::"r"(bar + 8 * NS), "r"(tok) : "memory");
                    mma(acc[0], va[0], p0.x & pmask, p0.y & pmask);
                    mma(acc[1], va[1], p0.x & pmask, p0.y & pmask);
                    mma(acc[2], va[2], p0.x & pmask, p0.y & pmask);
                    mma(acc[3], va[3], p0.x & pmask, p0.y & pmask);
                    mma(acc[0], va[4], p0.z & pmask, p0.w & pmask);
                    mma(acc[1], va[5], p0.z & pmask, p0.w & pmask);
                    mma(acc[2], va[6], p0.z & pmask, p0.w & pmask);
                    mma(acc[3], va[7], p0.z & pmask, p0.w & pmask);
                    pt[0] = p1.x & pmask;
                    pt[1] = p1.y & pmask;
                    pt[2] = p1.z & pmask;
                    pt[3] = p1.w & pmask;
                    psrc += 128;
                    bar = barn;
                    const uint32_t step = wrap ? -(NS - 1) * CHUNK : CHUNK;
#pragma unroll
                    for (int j = 0; j < 4; j++) cur[j] += step;
                }
#pragma unroll
                for (int j = 0; j < 8; j++) mma(acc[j & 3], vb[j], pt[(j >> 2) * 2], pt[(j >> 2) * 2 + 1]);
                float ev[4], od[4];
#pragma unroll
                for (int T = 0; T < 4; T++) {
                    ev[T] = acc[T][0] + acc[T][3];
                    od[T] = acc[T][1] + acc[T][2];
                }
                ev[0] += __shfl_xor_sync(0xffffffffu, ev[1], 1);
                od[0] += __shfl_xor_sync(0xffffffffu, od[1], 1);
                ev[2] += __shfl_xor_sync(0xffffffffu, ev[3], 1);
                od[2] += __shfl_xor_sync(0xffffffffu, od[3], 1);
                ev[0] += __shfl_xor_sync(0xffffffffu, ev[2], 2);
                od[0] += __shfl_xor_sync(0xffffffffu, od[2], 2);
                const float other = __shfl_xor_sync(0xffffffffu, (g & 1) ? ev[0] : od[0], 4);
                const uint32_t w = (g & 1) ? pack_bf(other, od[0]) : pack_bf(ev[0], other);
                xst32(odst, n ? w : EMPTY);
                __syncwarp();
                if (!n && lane == 0) mbar_arrive(sb + BAR_DRY);
                if (c < 112) {
                    bar_sync(1, 128);
                    if (tid == 0) {
                        const uint32_t on = n ? 0xffffffffu : 0u;
                        mbar_wait(sb + BAR_W0, ~on & 1);
                        l2_prefetch(p.w1 + c * 7168, 14336, on);
                        spin((is_f1 ? W1_DELAY : PF_DELAY) & on);
                        if (!is_f1) {
                            l2_prefetch(p.w2 + fi * 14336, 28672, on);
                            mbar_wait(sb + BAR_E1, ~on & 1);
                            spin(W2_DELAY & on);
                        }
                        tile_loads(sb + (n ? SM_WX : SM_WO + 8192), is_f1 ? &p.map_w1 : &p.map_w2,
                                   is_f1 ? fi * 32 : (fi % 28) * 16, n ? 0 : 1 << 20, is_f1 ? 64 : 224, is_f1 ? 4096 : 7168,
                                   sb + (n ? BAR_W1 : BAR_X), n ? 8 - is_f1 : 1);
                    }
                }
            }
        }
    } else {
        const int ew = warp - 5, et = tid - 160;
        const int r = lane & 7, mi = lane >> 3;
        {
            uint32_t w[7];
#pragma unroll
            for (int i = 0; i < 7; i++)
                asm volatile("ld.global.nc.u32 %0, [%1];" : "=r"(w[i]) : "l"((const uint32_t*)xin + ew * 224 + i * 32 + lane));
            bar_sync(0, NTHREADS);
            layernorm_row(w, sb + SM_XN + ew * 912, lane);
            mbar_wait(sb + BAR_WQ, 0);
            uint32_t a[8][4];
            frags_w448(a, sb + SM_WQ, ew, lane);
            const float2 q = gemv448(a, sb, ew, lane, et);
            if (et < 128) xst32(gx->q + ((et >> 4) * 16 + (c >> 3)) * 128 + (c & 7) * 16 + (et & 15), ~pack_bf(q.x, q.y));
        }
        const int hh = c / 7, jj = c - hh * 7;
        const int cg = fi % 28, half = fi / 28;
        const int ht0 = (c - 112) * 7 + min(ew, 6);
        uint32_t side;
        asm volatile("ld.global.nc.u32 %0, [%1];" : "=r"(side)
                     : "l"(c < 112 ? (is_f1 ? p.b1 + fi * 32 + (et & 15) * 2 : p.b2 + cg * 16 + r * 2)
                           : xin + ((ht0 & 6) + (mi & 1)) * DM + (ht0 >> 3) * 32 + (r & 3) * 8 + (ht0 & 1) * 4 + (r >> 2) * 2));
        uint32_t seen_prog = 0;
#pragma unroll 1
        for (int pass = 0; pass < 2; pass++) {
            uint32_t live = pass;
            asm volatile("" : "+r"(live));
            const uint32_t want = 0u - live, wipe = ~want;
            const int et = pin(tid - 160), ew = et >> 5, lane = et & 31;
            const int g = lane >> 2, t = lane & 3, r = lane & 7, mi = lane >> 3;
            if (et == 0) {
                if (!live) mbar_wait(sb + BAR_Q, 0);
#pragma unroll 1
                for (int it = 0; it < SPIN_LIMIT; it++) {
                    const uint32_t prog = ctl_load(sb + SM_PROG);
                    int total = 0;
                    if (prog == seen_prog) __nanosleep(100);
                    if (prog != seen_prog || prog >= 2 * NCH - 8)
                        asm volatile("ld.relaxed.gpu.global.u32 %0, [%1];" : "=r"(total) : "l"(gx->count + 32) : "memory");
                    if (total >= ALL_CHUNKS - LIFT_LEFT) {
                        ctl_store(sb + SM_DEPTH, NS);
                    } else if (prog != seen_prog) {
                        const int lead = prog * NCTA - total;
                        ctl_store(sb + SM_DEPTH, lead >= LEAD1 ? 1 : lead >= LEAD2 ? 2 : lead >= LEAD2 - 128 ? 3 : lead >= LEAD2 - 256 ? 4 : NS);
                    }
                    seen_prog = prog;
                    if (live ? total >= ALL_CHUNKS - (c < 112 ? TRIG_LEFT : 0) : mbar_test(sb + BAR_DRY, 0)) break;
                }
                tile_loads(sb + SM_WO, &p.map_wo, jj * 64, live ? hh * 256 : 1 << 20, 64, 8192, sb + (live ? BAR_WO : BAR_X + 8),
                           c >= 112 ? 0 : live ? 4 : 1);
            } else if (et == 32 && live) {
                uint32_t seen;
                mbar_wait(sb + BAR_DRY, 0);
                asm volatile("atom.release.gpu.global.add.u32 %0, [%1], 1;" : "=r"(seen) : "l"(gx->count) : "memory");
                int it = 0;
                for (seen++; seen < NCTA && ++it < SPIN_LIMIT;) {
                    __nanosleep(512);
                    asm volatile("ld.relaxed.gpu.global.u32 %0, [%1];" : "=r"(seen) : "l"(gx->count) : "memory");
                }
                asm volatile("ld.acquire.gpu.global.u32 %0, [%1];" : "=r"(seen) : "l"(gx->count) : "memory");
            }
            __syncwarp();
            bar_sync(2, 256);
            if (c >= 112) {
                if (ew < 7) {
                    const bool odd = mi & 1;
                    const int ht = (c - 112) * 7 + ew;
                    float a0, a1;
                    uint32_t* const dst = gx->h + pin((((mi >> 1) * 14 + (ht >> 3)) * 8 + (ht & 6) + (mi & 1)) * 16 + (ht & 1) * 8 + r);
                    Poll<4, 128> in(gx->part + pin(ht * 512 + lane * 4), want, want);
                    spin(R_DELAY & want);
                    in.finish([&] {
                        const uint4 (&v)[4] = in.v;
                        const float f0 = (__uint_as_float(v[0].x) + __uint_as_float(v[1].x)) + (__uint_as_float(v[2].x) + __uint_as_float(v[3].x));
                        const float f1 = (__uint_as_float(v[0].y) + __uint_as_float(v[1].y)) + (__uint_as_float(v[2].y) + __uint_as_float(v[3].y));
                        const float f2 = (__uint_as_float(v[0].z) + __uint_as_float(v[1].z)) + (__uint_as_float(v[2].z) + __uint_as_float(v[3].z));
                        const float f3 = (__uint_as_float(v[0].w) + __uint_as_float(v[1].w)) + (__uint_as_float(v[2].w) + __uint_as_float(v[3].w));
                        a0 = (odd ? f1 : f0) + __shfl_xor_sync(0xffffffffu, odd ? f0 : f1, 8);
                        a1 = (odd ? f3 : f2) + __shfl_xor_sync(0xffffffffu, odd ? f2 : f3, 8);
                    });
                    a0 += __shfl_xor_sync(0xffffffffu, a0, 16);
                    a1 += __shfl_xor_sync(0xffffffffu, a1, 16);
                    xst32(dst, bf2_add(side, pack_bf(a0, a1)) | wipe);
                }
                if (!live) bar_sync(3, 256);
                continue;
            }
            {
                const uint32_t fa = pin(sb + SM_WO + ((ew >> 1) * 64 + (mi >> 1) * 8 + r) * 128 + ((((ew & 1) * 4 + (mi & 1)) ^ r) << 4));
                const uint32_t wb = pin(sb + SM_RED + ((ew >> 1) * 544 + t * 136 + (ew & 1) * 64 + g * 2) * 4);
                const uint32_t rb = pin(sb + SM_RED + ((ew & 3) * 136 + ((ew >> 2) * 32 + (r >> 1) * 8 + mi * 2 + (r & 1)) * 2) * 4);
                uint32_t* const pdst = gx->part + pin((((jj * 8 + ew) * 2 + (lane >> 4)) * 16 + hh) * 32 + (lane & 15) * 2);
                Poll<2, 16> in(gx->o + pin((hh * 8 + g) * 128 + (ew >> 1) * 32 + t * 4), want, want);
                spin_or(O_DELAY & want, sb + BAR_WO + 8 * (ew >> 1));
                in.until(sb + BAR_WO + 8 * (ew >> 1));
                uint32_t a[8][4];
#pragma unroll
                for (int i = 0; i < 4; i++) {
                    const int ks = (i >> 1) + (i & 1) * 2;
                    ldsm4t(a[ks * 2], fa + ks * 2048);
                    ldsm4t(a[ks * 2 + 1], (fa ^ 32) + ks * 2048);
                }
                float acc[2][2][4];
                in.finish([&] {
#pragma unroll
                    for (int i = 0; i < 2; i++) {
                        mma0(acc[i][0], a[i * 4], in.v[i].x, in.v[i].y);
                        mma0(acc[i][1], a[i * 4 + 1], in.v[i].x, in.v[i].y);
                    }
#pragma unroll
                    for (int mt = 0; mt < 2; mt++) {
                        mma(acc[0][mt], a[2 + mt], in.v[0].z, in.v[0].w);
                        mma(acc[1][mt], a[6 + mt], in.v[1].z, in.v[1].w);
                    }
                });
#pragma unroll
                for (int mt = 0; mt < 2; mt++) {
                    sts64f(wb + mt * 128, acc[0][mt][0] + acc[1][mt][0], acc[0][mt][1] + acc[1][mt][1]);
                    sts64f(wb + mt * 128 + 64, acc[0][mt][2] + acc[1][mt][2], acc[0][mt][3] + acc[1][mt][3]);
                }
                bar_sync(2, 256);
                float2 v[4];
#pragma unroll
                for (int w = 0; w < 4; w++) v[w] = lds64f(rb + w * 2176);
                const float s0 = (v[0].x + v[1].x) + (v[2].x + v[3].x);
                const float s1 = (v[0].y + v[1].y) + (v[2].y + v[3].y);
                xst64(pdst, __float_as_uint(s0) | wipe, __float_as_uint(s1) | wipe);
            }
            if (et == 0 && live) mbar_arrive(sb + BAR_E1);
            const uint32_t wbar = sb + BAR_W1 + 8 * ew;
            if (is_f1) {
                constexpr uint32_t ONES = 0x3f803f80u;
                if (ew < 7) {
                    const int b = (et >> 4) & 7, pr = et & 15;
                    const uint32_t fa = pin(sb + SM_WX + (ew * 64 + (mi >> 1) * 8 + r) * 64 + (((mi & 1) ^ (r >> 1)) << 4));
                    const uint32_t wb = pin(sb + SM_RED + (ew * 288 + t * 72 + g) * 4);
                    const uint32_t sw = pin(sb + SM_RED + (ew * 288 + g * 36 + (t == (g >> 1) ? 32 : 34)) * 4);
                    const uint32_t rs = pin(sb + SM_RED + b * 144 + 128), rz = pin(sb + SM_RED + b * 144 + pr * 8);
                    const uint32_t cw = pin(sb + SM_XN + (ew * 32 + g + (t >> 1) * 16 + (t & 1) * 8) * 4), cr = pin(sb + SM_XN + pr * 8);
                    const bool odd = pin(g & 1);
                    uint32_t* const dst = gx->r + pin((((b >> 2) * 56 + fi) * 4 + (b & 3)) * 16 + (pr & 3) * 4 + (pr >> 2));
                    Poll<2, 128> in(gx->h + pin(((fi & 1) * 14 + ew * 2) * 128 + lane * 4), want, want);
                    mbar_wait(wbar, wipe & 1);
                    uint32_t a[8][4];
#pragma unroll
                    for (int ks = 0; ks < 4; ks++) {
                        ldsm4t(a[ks * 2], fa + ks * 1024);
                        ldsm4t(a[ks * 2 + 1], (fa ^ 32) + ks * 1024);
                    }
                    float cs[2][4] = {}, z[2][2][4], st[2][4];
#pragma unroll
                    for (int ks = 0; ks < 4; ks++) {
                        mma(cs[0], a[ks * 2], ONES, ONES);
                        mma(cs[1], a[ks * 2 + 1], ONES, ONES);
                    }
                    sts32f(cw, (t & 1) ? ((t & 2) ? cs[1][2] : cs[0][2]) : ((t & 2) ? cs[1][0] : cs[0][0]));
                    bar_sync(4, 224);
                    float2 cv[7];
#pragma unroll
                    for (int w = 0; w < 7; w++) cv[w] = lds64f(cr + w * 128);
                    const float cs0 = ((cv[0].x + cv[1].x) + (cv[2].x + cv[3].x)) + ((cv[4].x + cv[5].x) + cv[6].x);
                    const float cs1 = ((cv[0].y + cv[1].y) + (cv[2].y + cv[3].y)) + ((cv[4].y + cv[5].y) + cv[6].y);
                    in.finish([&] {
#pragma unroll
                        for (int i = 0; i < 2; i++) {
                            const uint32_t sa[4] = {in.v[i].x, ONES, in.v[i].y, ONES};
                            mma0(z[i][0], a[i * 4], in.v[i].x, in.v[i].y);
                            mma0(z[i][1], a[i * 4 + 1], in.v[i].x, in.v[i].y);
                            mma0(st[i], sa, in.v[i].x, in.v[i].y);
                        }
                    });
#pragma unroll
                    for (int i = 0; i < 2; i++) mma(z[i][0], a[i * 4 + 2], in.v[i].z, in.v[i].w);
#pragma unroll
                    for (int i = 0; i < 2; i++) mma(z[i][1], a[i * 4 + 3], in.v[i].z, in.v[i].w);
#pragma unroll
                    for (int i = 0; i < 2; i++) {
                        const uint32_t sa[4] = {in.v[i].z, ONES, in.v[i].w, ONES};
                        mma(st[i], sa, in.v[i].z, in.v[i].w);
                    }
#pragma unroll
                    for (int mt = 0; mt < 2; mt++) {
                        sts32f(wb + mt * 64, z[0][mt][0] + z[1][mt][0]);
                        sts32f(wb + mt * 64 + 144, z[0][mt][1] + z[1][mt][1]);
                        sts32f(wb + mt * 64 + 32, z[0][mt][2] + z[1][mt][2]);
                        sts32f(wb + mt * 64 + 176, z[0][mt][3] + z[1][mt][3]);
                    }
                    sts64f(sw, odd ? st[0][3] + st[1][3] : st[0][2] + st[1][2], odd ? st[0][1] + st[1][1] : st[0][0] + st[1][0]);
                    bar_sync(4, 224);
                    if (ew < 4) {
                        float2 sv[7], zv[7];
#pragma unroll
                        for (int w = 0; w < 7; w++) sv[w] = lds64f(rs + w * 1152);
#pragma unroll
                        for (int w = 0; w < 7; w++) zv[w] = lds64f(rz + w * 1152);
                        const float mu = (((sv[0].x + sv[1].x) + (sv[2].x + sv[3].x)) + ((sv[4].x + sv[5].x) + sv[6].x)) * (1.f / DM);
                        const float sq = ((sv[0].y + sv[1].y) + (sv[2].y + sv[3].y)) + ((sv[4].y + sv[5].y) + sv[6].y);
                        const float inv = inv_std(bf_round(fmaxf(fmaf(sq, 1.f / DM, -mu * mu), 0.f)));
                        const float mean = bf_round(mu);
                        const float z0 = ((zv[0].x + zv[1].x) + (zv[2].x + zv[3].x)) + ((zv[4].x + zv[5].x) + zv[6].x);
                        const float z1 = ((zv[0].y + zv[1].y) + (zv[2].y + zv[3].y)) + ((zv[4].y + zv[5].y) + zv[6].y);
                        const uint32_t u = pack_bf(fmaf(-mean, cs0, z0) * inv, fmaf(-mean, cs1, z1) * inv);
                        xst32(dst, bf2_relu_sq(bf2_add(u, side)) | wipe);
                    }
                    if (c == 0 && et == 128 && live) {
                        xst32(gx->count, 0);
                        xst32(gx->count + 32, 0);
                    }
                }
            } else {
                const uint32_t fa = pin(sb + SM_WX + (ew * 224 + (mi >> 1) * 8 + r) * 32 + (((mi & 1) ^ (r >> 2)) << 4));
                const uint32_t wb = pin(sb + SM_XN + (ew * 160 + (t & 1) * 80 + (g >> 1) * 4 + (t >> 1) * 2 + (g & 1)) * 4);
                const uint32_t rb = pin(sb + SM_XN + (mi * 40 + r * 4) * 4);
                const bool upper = pin(t >> 1), first = pin(ew == 0);
                uint32_t* const dst = (live ? (uint32_t*)p.out : gx->sink) + pin((half * 4 + mi) * 224 + cg * 8 + r);
                Poll<4, 128, true> in(gx->r + pin((half * 56 + ew * 7) * 64 + lane * 4), want, lane < 16 ? want : 0u,
                                      gx->h + pin((((fi & 1) * 14 + (cg >> 1)) * 8 + half * 4 + mi) * 16 + (r & 3) * 4 +
                                                  (cg & 1) * 2 + (r >> 2)),
                                      ew == 0 ? want : 0u);
                mbar_wait(wbar, wipe & 1);
                uint32_t a[14][4];
#pragma unroll
                for (int ks = 0; ks < 14; ks++) ldsm4t(a[ks], fa + ks * 512);
                float acc[4][4];
                const auto step = [&](int i) {
                    mma(acc[0], a[4 * i], in.v[i].x, in.v[i].y);
                    mma(acc[1], a[4 * i + 1], in.v[i].z, in.v[i].w);
                    if (i < 3) {
                        mma(acc[2], a[4 * i + 2], in.v[i].x, in.v[i].y);
                        mma(acc[3], a[4 * i + 3], in.v[i].z, in.v[i].w);
                    }
                };
                in.finish([&] {
                    mma0(acc[0], a[0], in.v[0].x, in.v[0].y);
                    mma0(acc[1], a[1], in.v[0].z, in.v[0].w);
                    mma0(acc[2], a[2], in.v[0].x, in.v[0].y);
                    mma0(acc[3], a[3], in.v[0].z, in.v[0].w);
                    step(1);
                });
                step(2);
                step(3);
                sts32f(wb, upper ? acc[2][0] + acc[3][0] : acc[0][0] + acc[1][0]);
                sts32f(wb + 160, upper ? acc[2][1] + acc[3][1] : acc[0][1] + acc[1][1]);
                sts32f(wb + 64, upper ? acc[2][2] + acc[3][2] : acc[0][2] + acc[1][2]);
                sts32f(wb + 224, upper ? acc[2][3] + acc[3][3] : acc[0][3] + acc[1][3]);
                bar_sync(2, 256);
                if (first) {
                    float x[8], y[8];
#pragma unroll
                    for (int w = 0; w < 8; w++) {
                        const uint4 q = lds128(rb + w * 640);
                        x[w] = __uint_as_float(q.x) + __uint_as_float(q.z);
                        y[w] = __uint_as_float(q.y) + __uint_as_float(q.w);
                    }
                    const float s0 = ((x[0] + x[1]) + (x[2] + x[3])) + ((x[4] + x[5]) + (x[6] + x[7]));
                    const float s1 = ((y[0] + y[1]) + (y[2] + y[3])) + ((y[4] + y[5]) + (y[6] + y[7]));
                    *dst = bf2_add(in.word, bf2_add(pack_bf(s0, s1), side));
                }
                exit_if(live);
            }
            if (!live) bar_sync(3, 256);
        }
    }
}

using EncodeFn = CUresult (*)(CUtensorMap*, CUtensorMapDataType, cuuint32_t, void*, const cuuint64_t*, const cuuint64_t*,
                              const cuuint32_t*, const cuuint32_t*, CUtensorMapInterleave, CUtensorMapSwizzle,
                              CUtensorMapL2promotion, CUtensorMapFloatOOBfill);

void encode_map(EncodeFn fn, CUtensorMap* map, const void* base, int rows, int cols, int box_rows, int box_cols,
                CUtensorMapSwizzle swizzle) {
    const cuuint64_t dims[2] = {(cuuint64_t)cols, (cuuint64_t)rows};
    const cuuint64_t strides[1] = {(cuuint64_t)cols * 2};
    const cuuint32_t box[2] = {(cuuint32_t)box_cols, (cuuint32_t)box_rows};
    const cuuint32_t steps[2] = {1, 1};
    fn(map, CU_TENSOR_MAP_DATA_TYPE_BFLOAT16, 2, const_cast<void*>(base), dims, strides, box, steps,
       CU_TENSOR_MAP_INTERLEAVE_NONE, swizzle, CU_TENSOR_MAP_L2_PROMOTION_L2_128B, CU_TENSOR_MAP_FLOAT_OOB_FILL_NONE);
}

}

extern "C" void kernel_launch(void* const* d_in, const int* in_sizes, int n_in, void* d_out, int out_size) {
    (void)in_sizes; (void)n_in; (void)out_size;
    Params p;
    p.w1 = (const __nv_bfloat16*)d_in[6];
    p.b1 = (const __nv_bfloat16*)d_in[7];
    p.w2 = (const __nv_bfloat16*)d_in[8];
    p.b2 = (const __nv_bfloat16*)d_in[9];
    p.out = (__nv_bfloat16*)d_out;
    Exchange* xch = nullptr;
    cudaGetSymbolAddress((void**)&xch, g_x);
    void* fn = nullptr;
    cudaDriverEntryPointQueryResult found;
    cudaGetDriverEntryPoint("cuTensorMapEncodeTiled", &fn, cudaEnableDefault, &found);
    encode_map((EncodeFn)fn, &p.map_wo, d_in[4], NH * DH, DM, 64, 64, CU_TENSOR_MAP_SWIZZLE_128B);
    encode_map((EncodeFn)fn, &p.map_w1, p.w1, DM, FF, 64, 32, CU_TENSOR_MAP_SWIZZLE_64B);
    encode_map((EncodeFn)fn, &p.map_w2, p.w2, FF, DM, 224, 16, CU_TENSOR_MAP_SWIZZLE_32B);
    cudaFuncSetAttribute(fused_decode_kernel, cudaFuncAttributeMaxDynamicSharedMemorySize, SM_TOTAL);
    fused_decode_kernel<<<NCTA, NTHREADS, SM_TOTAL>>>((const __nv_bfloat16*)d_in[3], (const __nv_bfloat16*)d_in[0],
                                                      (const char*)d_in[1], (const char*)d_in[2], xch, p);
}
```

```cpp
#include <cuda.h>
#include <cuda_runtime.h>
#include <cuda_bf16.h>
#include <stdint.h>

namespace {

constexpr int DM = 448, NH = 16, SK = 4096, DH = 256, FF = 1792;
constexpr int NCTA = 128;
constexpr int CHUNK = 32768;
constexpr int NCH = SK / 64;
constexpr int NS = 5;
constexpr int ALL_CHUNKS = NCTA * 2 * NCH;
constexpr int LEAD1 = 128;
constexpr int LEAD2 = -128;
constexpr int LIFT_LEFT = 370;
constexpr int TRIG_LEFT = 220;
constexpr int K1_DELAY = 1000;
constexpr int Q_SLEEP = 100;
constexpr int W1_DELAY = 600;
constexpr int PF_DELAY = 500;
constexpr int W2_DELAY = 600;
constexpr int ROT = 32;
constexpr int R_DELAY = 200;
constexpr int O_DELAY = 1600;
constexpr int NTHREADS = 13 * 32;
constexpr int SPIN_LIMIT = 1 << 18;
constexpr int WAIT_LIMIT = 1 << 15;

constexpr int SM_RING = 0;
constexpr int SM_WX = 0;
constexpr int SM_WQ = NS * CHUNK;
constexpr int SM_WO = SM_WQ;
constexpr int SM_P = SM_WQ + 32768;
constexpr int SM_RED = SM_P + 8192;
constexpr int SM_XN = SM_RED + 4 * 544 * 4;
constexpr int SM_Q = SM_XN + 8 * 456 * 2;
constexpr int SM_STAT = SM_Q + 512;
constexpr int SM_PROG = SM_STAT + 32, SM_DEPTH = SM_STAT + 36;
constexpr int SM_BAR = SM_STAT + 64;
constexpr int BAR_FULL = SM_BAR, BAR_EMPTY = BAR_FULL + 8 * NS, BAR_WO = BAR_EMPTY + 8 * NS, BAR_DRY = BAR_WO + 32,
              BAR_WQ = BAR_DRY + 8, BAR_Q = BAR_WQ + 8, BAR_W0 = BAR_WO + 24, BAR_E1 = BAR_Q + 8, BAR_X = BAR_E1 + 8,
              BAR_QP = BAR_X + 16, BAR_W1 = BAR_QP + 8;
constexpr int SM_TOTAL = BAR_W1 + 64;
static_assert(SM_TOTAL <= 232448, "shared memory budget");

struct Exchange {
    uint32_t q[NCTA * 128];
    uint32_t o[NH * 8 * 128];
    uint32_t part[14 * 8 * 16 * 32];
    uint32_t h[2 * 14 * 8 * 16];
    uint32_t r[2 * 56 * 4 * 16];
    uint32_t count[64];
    uint32_t sink[8 * 224];
};
__device__ __align__(128) Exchange g_x;

__device__ __forceinline__ void mbar_init(uint32_t bar, uint32_t count) {
    asm volatile("mbarrier.init.shared::cta.b64 [%0], %1;" ::"r"(bar), "r"(count) : "memory");
}
__device__ __forceinline__ void mbar_arrive(uint32_t bar) {
    asm volatile("mbarrier.arrive.shared::cta.b64 _, [%0];" ::"r"(bar) : "memory");
}
__device__ __forceinline__ void mbar_expect_tx(uint32_t bar, uint32_t bytes) {
    asm volatile("mbarrier.arrive.expect_tx.shared::cta.b64 _, [%0], %1;" ::"r"(bar), "r"(bytes) : "memory");
}
__device__ __forceinline__ void mbar_wait(uint32_t bar, uint32_t parity) {
    asm volatile("{\n.reg .pred p, q;\n.reg .u32 n;\nmov.u32 n, %2;\n"
                 "RETRY:\nsub.u32 n, n, 1;\nsetp.ne.u32 q, n, 0;\n"
                 "mbarrier.try_wait.parity.shared::cta.b64 p, [%0], %1;\nand.pred q, q, !p;\n@q bra RETRY;\n}"
                 ::"r"(bar), "r"(parity), "n"(WAIT_LIMIT) : "memory");
}
__device__ __forceinline__ uint32_t mbar_test(uint32_t bar, uint32_t parity) {
    uint32_t done;
    asm volatile("{\n.reg .pred p;\nmbarrier.test_wait.parity.shared::cta.b64 p, [%1], %2;\nselp.u32 %0, 1, 0, p;\n}"
                 : "=r"(done) : "r"(bar), "r"(parity) : "memory");
    return done;
}
__device__ __forceinline__ void exit_if(uint32_t on) {
    asm volatile("{\n.reg .pred p;\nsetp.ne.u32 p, %0, 0;\n@p exit;\n}" ::"r"(on) : "memory");
}
__device__ __forceinline__ void spin(uint32_t cycles) {
    const uint32_t t0 = (uint32_t)clock();
    do {
    } while ((uint32_t)clock() - t0 < cycles);
}
__device__ __forceinline__ void spin_or(uint32_t cycles, uint32_t bar) {
    const uint32_t t0 = (uint32_t)clock();
    do {
    } while (!mbar_test(bar, 0) && (uint32_t)clock() - t0 < cycles);
}
__device__ __forceinline__ void l2_prefetch(const void* src, uint32_t bytes, uint32_t on) {
    asm volatile("{\n.reg .pred p;\nsetp.ne.u32 p, %2, 0;\n@p cp.async.bulk.prefetch.L2.global [%0], %1;\n}"
                 ::"l"(src), "r"(bytes), "r"(on) : "memory");
}
__device__ __forceinline__ void bulk_load(uint32_t dst, const void* src, uint32_t bytes, uint32_t bar, uint64_t pol) {
    asm volatile("cp.async.bulk.shared::cluster.global.mbarrier::complete_tx::bytes.L2::cache_hint [%0], [%1], %2, [%3], %4;"
                 ::"r"(dst), "l"(src), "r"(bytes), "r"(bar), "l"(pol) : "memory");
}
__device__ __forceinline__ void tile_loads(uint32_t dst, const CUtensorMap* map, int col, int row, int rows, uint32_t bytes,
                                           uint32_t bar, int n) {
#pragma unroll 1
    for (int i = 0; i < n; i++, dst += bytes, row += rows, bar += 8) {
        mbar_expect_tx(bar, bytes);
        asm volatile("cp.async.bulk.tensor.2d.shared::cluster.global.mbarrier::complete_tx::bytes [%0], [%1, {%2, %3}], [%4];"
                     ::"r"(dst), "l"(map), "r"(col), "r"(row), "r"(bar) : "memory");
    }
}
__device__ __forceinline__ void bar_sync(int id, int n) { asm volatile("bar.sync %0, %1;" ::"r"(id), "r"(n) : "memory"); }

__device__ __forceinline__ void ldsm4(uint32_t (&r)[4], uint32_t a) {
    asm volatile("ldmatrix.sync.aligned.m8n8.x4.shared.b16 {%0,%1,%2,%3}, [%4];"
                 : "=r"(r[0]), "=r"(r[1]), "=r"(r[2]), "=r"(r[3]) : "r"(a) : "memory");
}
__device__ __forceinline__ void ldsm4t(uint32_t (&r)[4], uint32_t a) {
    asm volatile("ldmatrix.sync.aligned.m8n8.x4.trans.shared.b16 {%0,%1,%2,%3}, [%4];"
                 : "=r"(r[0]), "=r"(r[1]), "=r"(r[2]), "=r"(r[3]) : "r"(a) : "memory");
}
__device__ __forceinline__ void mma(float (&c)[4], const uint32_t (&a)[4], uint32_t b0, uint32_t b1) {
    asm volatile("mma.sync.aligned.m16n8k16.row.col.f32.bf16.bf16.f32 {%0,%1,%2,%3}, {%4,%5,%6,%7}, {%8,%9}, {%0,%1,%2,%3};"
                 : "+f"(c[0]), "+f"(c[1]), "+f"(c[2]), "+f"(c[3])
                 : "r"(a[0]), "r"(a[1]), "r"(a[2]), "r"(a[3]), "r"(b0), "r"(b1));
}
__device__ __forceinline__ void mma0(float (&c)[4], const uint32_t (&a)[4], uint32_t b0, uint32_t b1) {
    asm volatile("mma.sync.aligned.m16n8k16.row.col.f32.bf16.bf16.f32 {%0,%1,%2,%3}, {%4,%5,%6,%7}, {%8,%9}, {%10,%10,%10,%10};"
                 : "=f"(c[0]), "=f"(c[1]), "=f"(c[2]), "=f"(c[3])
                 : "r"(a[0]), "r"(a[1]), "r"(a[2]), "r"(a[3]), "r"(b0), "r"(b1), "f"(0.f));
}
__device__ __forceinline__ uint32_t lds32(uint32_t a) {
    uint32_t v;
    asm volatile("ld.shared.u32 %0, [%1];" : "=r"(v) : "r"(a) : "memory");
    return v;
}
__device__ __forceinline__ uint32_t ctl_load(uint32_t a) {
    uint32_t v;
    asm volatile("ld.volatile.shared.u32 %0, [%1];" : "=r"(v) : "r"(a) : "memory");
    return v;
}
__device__ __forceinline__ void ctl_store(uint32_t a, uint32_t v) {
    asm volatile("st.volatile.shared.u32 [%0], %1;" ::"r"(a), "r"(v) : "memory");
}
__device__ __forceinline__ float2 lds64f(uint32_t a) {
    float2 v;
    asm volatile("ld.shared.v2.f32 {%0,%1}, [%2];" : "=f"(v.x), "=f"(v.y) : "r"(a) : "memory");
    return v;
}
__device__ __forceinline__ uint4 lds128(uint32_t a) {
    uint4 v;
    asm volatile("ld.shared.v4.u32 {%0,%1,%2,%3}, [%4];" : "=r"(v.x), "=r"(v.y), "=r"(v.z), "=r"(v.w) : "r"(a) : "memory");
    return v;
}
__device__ __forceinline__ void sts16(uint32_t a, uint32_t v) {
    asm volatile("st.shared.u16 [%0], %1;" ::"r"(a), "h"((unsigned short)v) : "memory");
}
__device__ __forceinline__ void sts32(uint32_t a, uint32_t v) {
    asm volatile("st.shared.u32 [%0], %1;" ::"r"(a), "r"(v) : "memory");
}
__device__ __forceinline__ void sts32f(uint32_t a, float v) {
    asm volatile("st.shared.f32 [%0], %1;" ::"r"(a), "f"(v) : "memory");
}
__device__ __forceinline__ void sts64f(uint32_t a, float x, float y) {
    asm volatile("st.shared.v2.f32 [%0], {%1,%2};" ::"r"(a), "f"(x), "f"(y) : "memory");
}
__device__ __forceinline__ void sts128(uint32_t a, uint4 v) {
    asm volatile("st.shared.v4.u32 [%0], {%1,%2,%3,%4};" ::"r"(a), "r"(v.x), "r"(v.y), "r"(v.z), "r"(v.w) : "memory");
}

constexpr uint32_t EMPTY = 0xffffffffu;
__device__ __forceinline__ void xld32(uint32_t& v, const uint32_t* p, uint32_t empty) {
    asm volatile("{\n.reg .pred p;\nsetp.eq.u32 p, %0, %2;\n@p ld.relaxed.gpu.global.u32 %0, [%1];\n}"
                 : "+r"(v) : "l"(p), "r"(empty) : "memory");
}
__device__ __forceinline__ void xld128(uint4& v, const uint32_t* p, uint32_t top) {
    asm volatile("{\n.reg .pred p;\nsetp.eq.u32 p, %5, 0xffffffff;\n@p ld.relaxed.gpu.global.v4.u32 {%0,%1,%2,%3}, [%4];\n}"
                 : "+r"(v.x), "+r"(v.y), "+r"(v.z), "+r"(v.w) : "l"(p), "r"(top) : "memory");
}
__device__ __forceinline__ void xst32(uint32_t* p, uint32_t v) {
    asm volatile("st.relaxed.gpu.global.u32 [%0], %1;" ::"l"(p), "r"(v) : "memory");
}
__device__ __forceinline__ void xst64(uint32_t* p, uint32_t a, uint32_t b) {
    asm volatile("st.relaxed.gpu.global.v2.u32 [%0], {%1,%2};" ::"l"(p), "r"(a), "r"(b) : "memory");
}
__device__ __forceinline__ uint32_t top_word(const uint4& v) { return max(__vimax3_u32(v.x, v.y, v.z), v.w); }
template <int N, int STRIDE, bool WORD = false>
struct Poll {
    uint4 v[N];
    uint32_t top[N], word, want;
    const uint32_t *src, *wsrc;
    int left;
    __device__ __forceinline__ Poll(const uint32_t* s, uint32_t init, uint32_t init_last, const uint32_t* ws = nullptr,
                                    uint32_t init_word = 0)
        : word(init_word), want(init), src(s), wsrc(ws), left(init ? SPIN_LIMIT : 2) {
#pragma unroll
        for (int i = 0; i < N; i++) {
            top[i] = i == N - 1 ? init_last : init;
            v[i] = make_uint4(top[i], top[i], top[i], top[i]);
        }
    }
    __device__ __forceinline__ void issue() {
#pragma unroll
        for (int i = 0; i < N; i++) xld128(v[i], src + i * STRIDE, top[i]);
        if (WORD) xld32(word, wsrc, EMPTY);
        left--;
    }
    __device__ __forceinline__ bool missing() {
        uint32_t m = WORD ? word : 0;
#pragma unroll
        for (int i = 0; i < N; i++) {
            top[i] = top_word(v[i]);
            m = max(m, top[i]);
        }
        return __any_sync(0xffffffffu, m == want && left > 0);
    }
    __device__ __forceinline__ void until(uint32_t bar) {
#pragma unroll 1
        while (!mbar_test(bar, 0)) {
            issue();
            if (!missing()) break;
        }
        mbar_wait(bar, ~want & 1);
    }
    template <class F>
    __device__ __forceinline__ void finish(F use) {
        bool again;
#pragma unroll 1
        do {
            issue();
            again = missing();
            use();
        } while (again);
    }
};
__device__ __forceinline__ uint32_t pin(uint32_t v) {
    asm volatile("shfl.sync.bfly.b32 %0, %0, 0, 0x1f, 0xffffffff;" : "+r"(v));
    return v;
}
__device__ __forceinline__ uint32_t bf2_add(uint32_t a, uint32_t b) {
    uint32_t r;
    asm("add.rn.bf16x2 %0, %1, %2;" : "=r"(r) : "r"(a), "r"(b));
    return r;
}
__device__ __forceinline__ uint32_t bf2_relu_sq(uint32_t a) {
    uint32_t r;
    asm("{\n.reg .b32 m;\nmax.bf16x2 m, %1, %2;\nmul.rn.bf16x2 %0, m, m;\n}" : "=r"(r) : "r"(a), "r"(0));
    return r;
}

__device__ __forceinline__ uint32_t pack_bf(float lo, float hi) {
    uint32_t r;
    asm("cvt.rn.bf16x2.f32 %0, %1, %2;" : "=r"(r) : "f"(hi), "f"(lo));
    return r;
}
__device__ __forceinline__ float bf_round(float v) { return __uint_as_float(pack_bf(0.f, v)); }
__device__ __forceinline__ float bf_lo(uint32_t w) { return __uint_as_float(w << 16); }
__device__ __forceinline__ float bf_hi(uint32_t w) { return __uint_as_float(w & 0xffff0000u); }

__device__ __forceinline__ float inv_std(float var) {
    float sd, inv;
    asm("sqrt.approx.ftz.f32 %0, %1;" : "=f"(sd) : "f"(bf_round(var + 1e-5f)));
    asm("rcp.approx.ftz.f32 %0, %1;" : "=f"(inv) : "f"(bf_round(sd)));
    return inv;
}

__device__ __forceinline__ void layernorm_row(const uint32_t (&w)[7], uint32_t dst, int lane) {
    const float shift = bf_lo(__shfl_sync(0xffffffffu, w[0], 0));
    float s = 0.f, ss = 0.f;
#pragma unroll
    for (int i = 0; i < 7; i++) {
        const float a = bf_lo(w[i]) - shift, b = bf_hi(w[i]) - shift;
        s += a + b;
        ss = fmaf(a, a, fmaf(b, b, ss));
    }
#pragma unroll
    for (int o = 16; o; o >>= 1) {
        s += __shfl_xor_sync(0xffffffffu, s, o);
        ss += __shfl_xor_sync(0xffffffffu, ss, o);
    }
    const float md = s * (1.f / DM);
    const float mean = bf_round(shift + md);
    const float inv = inv_std(bf_round(fmaxf(ss * (1.f / DM) - md * md, 0.f)));
#pragma unroll
    for (int i = 0; i < 7; i++) {
        const float a = bf_round(bf_lo(w[i]) - mean) * inv, b = bf_round(bf_hi(w[i]) - mean) * inv;
        sts32(dst + (i * 32 + lane) * 4, pack_bf(a, b));
    }
}

__device__ __forceinline__ void frags_w448(uint32_t (&a)[8][4], uint32_t src, int ew, int lane) {
    const int r = lane & 7, mi = lane >> 3;
    const uint32_t base = src + ((ew < 7 ? ew : 0) * 64 + (mi >> 1) * 8 + r) * 64;
#pragma unroll
    for (int ks = 0; ks < 4; ks++)
#pragma unroll
        for (int mt = 0; mt < 2; mt++)
            ldsm4t(a[ks * 2 + mt], base + ks * 1024 + (((2 * mt + (mi & 1)) ^ (r >> 1)) << 4));
}
__device__ __forceinline__ float2 gemv448(const uint32_t (&a)[8][4], uint32_t sb, int ew, int lane, int et) {
    const int g = lane >> 2, t = lane & 3;
    bar_sync(2, 256);
    if (ew < 7) {
        float c[4][4] = {};
        const uint32_t xb = sb + SM_XN + (g * 228 + ew * 32 + t) * 4;
#pragma unroll
        for (int ks = 0; ks < 4; ks++) {
            const uint32_t b0 = lds32(xb + ks * 32), b1 = lds32(xb + ks * 32 + 16);
            mma(c[(ks & 1) * 2], a[ks * 2], b0, b1);
            mma(c[(ks & 1) * 2 + 1], a[ks * 2 + 1], b0, b1);
        }
        const uint32_t rb = sb + SM_RED + (ew * 288 + t * 72 + g) * 4;
#pragma unroll
        for (int mt = 0; mt < 2; mt++) {
            sts32f(rb + mt * 64, c[mt][0] + c[2 + mt][0]);
            sts32f(rb + mt * 64 + 144, c[mt][1] + c[2 + mt][1]);
            sts32f(rb + mt * 64 + 32, c[mt][2] + c[2 + mt][2]);
            sts32f(rb + mt * 64 + 176, c[mt][3] + c[2 + mt][3]);
        }
    }
    bar_sync(2, 256);
    float2 acc = make_float2(0.f, 0.f);
    if (et < 128) {
        const uint32_t rb = sb + SM_RED + ((et >> 4) * 36 + (et & 15) * 2) * 4;
#pragma unroll
        for (int w = 0; w < 7; w++) {
            const float2 v = lds64f(rb + w * 1152);
            acc.x += v.x;
            acc.y += v.y;
        }
    }
    return acc;
}

struct Params {
    const __nv_bfloat16 *w1, *b1, *w2, *b2;
    __nv_bfloat16* out;
    alignas(64) CUtensorMap map_wo, map_w1, map_w2;
};

__global__ void __launch_bounds__(NTHREADS, 1)
fused_decode_kernel(const __nv_bfloat16* const wq, const __nv_bfloat16* const xin, const char* const kc, const char* const vc,
                    Exchange* const gx, const __grid_constant__ Params p) {
    extern __shared__ __align__(1024) unsigned char smem[];
    const uint32_t sb = (uint32_t)__cvta_generic_to_shared(smem);
    const int tid = threadIdx.x, warp = tid >> 5, lane = tid & 31;
    const int c = blockIdx.x;
    const char* kbase = kc + (size_t)c * (SK * DH * 2);
    const char* vbase = vc + (size_t)c * (SK * DH * 2);

    const int rot = (c * ROT) & (NCH - 1);
    const bool is_f1 = !(c & 1);
    const int fi = c >> 1;

    asm volatile("{\n.reg .pred p;\n.reg .b32 w;\n.reg .b64 a;\nmov.u32 w, %%ctaid.x;\nmad.wide.u32 a, w, 28672, %0;\n"
                 "setp.eq.u32 p, %1, 128;\n@p cp.async.bulk.prefetch.L2.global [a], 28672;\n}"
                 ::"l"(wq), "r"(tid) : "memory");
    uint64_t pol = 0;
    if (tid == 128) {
        mbar_init(sb + BAR_FULL, 1);
        asm volatile("fence.mbarrier_init.release.cluster;" ::: "memory");
        asm volatile("createpolicy.fractional.L2::evict_first.b64 %0, 1.0;" : "=l"(pol));
        mbar_expect_tx(sb + BAR_FULL, CHUNK);
        bulk_load(sb + SM_RING, kbase + rot * CHUNK, CHUNK, sb + BAR_FULL, pol);
    }
    if (warp == 4) {
        if (lane == 0) {
#pragma unroll
            for (int s = 0; s < NS; s++) {
                if (s) mbar_init(sb + BAR_FULL + 8 * s, 1);
                mbar_init(sb + BAR_EMPTY + 8 * s, 4);
            }
#pragma unroll
            for (int w = 0; w < 8; w++) {
                if (w < 4) mbar_init(sb + BAR_WO + 8 * w, 1);
                mbar_init(sb + BAR_W1 + 8 * w, 1);
            }
            mbar_init(sb + BAR_DRY, 4);
            mbar_init(sb + BAR_WQ, 128);
            mbar_init(sb + BAR_Q, 1);
            mbar_init(sb + BAR_QP, 1);
            mbar_init(sb + BAR_E1, 1);
            mbar_init(sb + BAR_X, 1);
            mbar_init(sb + BAR_X + 8, 1);
            ctl_store(sb + SM_PROG, 0);
            ctl_store(sb + SM_DEPTH, 2);
            asm volatile("fence.mbarrier_init.release.cluster;" ::: "memory");
        }
        __syncwarp();
        asm volatile("bar.arrive 0, %0;" ::"n"(NTHREADS) : "memory");
        if (lane == 0) {
            spin_or(K1_DELAY, sb + BAR_WQ);
            int s = 1, sl = 0, landed = 0;
            uint32_t ph = 1, phl = 0;
#pragma unroll 1
            for (int i = 1; i <= 2 * NCH; i++) {
                const char* src = (i < NCH ? kbase : vbase) + ((i + rot) & (NCH - 1)) * CHUNK;
                for (int it = 0; landed < (i < 2 * NCH ? i + 1 - (int)ctl_load(sb + SM_DEPTH) : i); it++) {
                    if (mbar_test(sb + BAR_FULL + 8 * sl, phl) || it >= 4 * SPIN_LIMIT) {
                        asm volatile("red.relaxed.gpu.global.add.u32 [%0], 1;" ::"l"(gx->count + 32) : "memory");
                        ctl_store(sb + SM_PROG, ++landed);
                        if (++sl == NS) { sl = 0; phl ^= 1; }
                    } else {
                        __nanosleep(20);
                    }
                }
                if (i == 2 * NCH) break;
                mbar_wait(sb + BAR_EMPTY + 8 * s, ph);
                mbar_expect_tx(sb + BAR_FULL + 8 * s, CHUNK);
                bulk_load(sb + SM_RING + s * CHUNK, src, CHUNK, sb + BAR_FULL + 8 * s, pol);
                if (++s == NS) { s = 0; ph ^= 1; }
            }
        }
    } else if (warp < 4) {
        const int g = lane >> 2, t = lane & 3, r = lane & 7, mi = lane >> 3;
        {
            const int row = tid >> 2, ch = tid & 3;
            const uint32_t dst = sb + SM_WQ + row * 64 + ((ch ^ ((row >> 1) & 3)) << 4);
            const __nv_bfloat16* src = wq + row * (NH * DH) + c * 32 + ch * 8;
#pragma unroll
            for (int i = 0; i < 14; i++)
                asm volatile("cp.async.cg.shared.global [%0], [%1], 16;" ::"r"(dst + i * 2048), "l"(src + i * 32 * (NH * DH)) : "memory");
            uint32_t* slot = gx->q + c * 128 + tid;
            uint32_t w = 0;
#pragma unroll 1
            for (int it = 0; it < SPIN_LIMIT; it++) {
                xld32(w, slot, 0);
                if (it == 0) {
                    bar_sync(0, NTHREADS);
                    asm volatile("cp.async.mbarrier.arrive.noinc.shared::cta.b64 [%0];" ::"r"(sb + BAR_WQ) : "memory");
                }
                if (!__any_sync(0xffffffffu, w == 0)) break;
                __nanosleep(Q_SLEEP);
            }
            xst32(slot, 0);
            sts32(sb + SM_Q + tid * 4, ~w);
        }
        bar_sync(1, 128);
        if (tid == 0) mbar_arrive(sb + BAR_Q);
        int s = 0;
        uint32_t ph = 0;
        float rmax = -INFINITY;
        {
            uint32_t qf[32];
#pragma unroll
            for (int i = 0; i < 32; i++) qf[i] = lds32(sb + SM_Q + ((i ^ g) * 4 + t) * 4);
            uint32_t off[4];
#pragma unroll
            for (int i = 0; i < 4; i++)
                off[i] = sb + SM_RING + (warp * 16 + (mi & 1) * 8 + r) * 512 + (((2 * i + (mi >> 1)) ^ r) << 4);
            const bool owner = t == (g >> 1);
            uint32_t pdst = sb + SM_P + (t * 16 + warp * 4 + (g & 1)) * 2;
#pragma unroll 1
            for (int i = 0; i < NCH; i++) {
                mbar_wait(sb + BAR_FULL + 8 * s, ph);
                float acc[4][4] = {};
#pragma unroll
                for (int ks = 0; ks < 16; ks++) {
                    uint32_t a[4];
                    ldsm4(a, off[ks & 3] + s * CHUNK + (ks >> 2) * 128);
                    mma(acc[ks & 3], a, qf[2 * ks], qf[2 * ks + 1]);
                }
                __syncwarp();
                if (lane == 0) mbar_arrive(sb + BAR_EMPTY + 8 * s);
                float v[4];
#pragma unroll
                for (int e = 0; e < 4; e++) v[e] = (acc[0][e] + acc[1][e]) + (acc[2][e] + acc[3][e]);
                const float lo = (g & 1) ? v[1] : v[0], hi = (g & 1) ? v[3] : v[2];
                const uint32_t sc = pack_bf(bf_round(lo) * 0.0625f, bf_round(hi) * 0.0625f);
                if (owner) {
                    sts16(pdst, sc & 0xffffu);
                    sts16(pdst + 4, sc >> 16);
                    rmax = fmaxf(rmax, fmaxf(bf_lo(sc), bf_hi(sc)));
                }
                pdst += 128;
                if (++s == NS) { s = 0; ph ^= 1; }
            }
        }
        mbar_wait(sb + BAR_QP, 0);
        asm volatile("fence.proxy.async.shared::cta;" ::: "memory");
        {
#pragma unroll
            for (int o = 16; o; o >>= 1) rmax = fmaxf(rmax, __shfl_xor_sync(0xffffffffu, rmax, o));
            if (lane == 0) sts32f(sb + SM_STAT + warp * 4, rmax);
            bar_sync(1, 128);
            const uint4 mx = lds128(sb + SM_STAT);
            const float m = fmaxf(fmaxf(__uint_as_float(mx.x), __uint_as_float(mx.y)),
                                  fmaxf(__uint_as_float(mx.z), __uint_as_float(mx.w)));
            float e[32];
            float sum = 0.f;
#pragma unroll
            for (int i = 0; i < 4; i++) {
                const uint4 w = lds128(sb + SM_P + (i * 128 + tid) * 16);
                const uint32_t ww[4] = {w.x, w.y, w.z, w.w};
#pragma unroll
                for (int j = 0; j < 4; j++) {
                    e[i * 8 + 2 * j] = __expf(bf_lo(ww[j]) - m);
                    e[i * 8 + 2 * j + 1] = __expf(bf_hi(ww[j]) - m);
                    sum += e[i * 8 + 2 * j] + e[i * 8 + 2 * j + 1];
                }
            }
#pragma unroll
            for (int o = 16; o; o >>= 1) sum += __shfl_xor_sync(0xffffffffu, sum, o);
            if (lane == 0) sts32f(sb + SM_STAT + 16 + warp * 4, sum);
            bar_sync(1, 128);
            const uint4 sm = lds128(sb + SM_STAT + 16);
            const float inv = 1.f / ((__uint_as_float(sm.x) + __uint_as_float(sm.y)) +
                                     (__uint_as_float(sm.z) + __uint_as_float(sm.w)));
#pragma unroll
            for (int i = 0; i < 4; i++) {
                uint4 w;
                w.x = pack_bf(e[i * 8 + 0] * inv, e[i * 8 + 1] * inv);
                w.y = pack_bf(e[i * 8 + 2] * inv, e[i * 8 + 3] * inv);
                w.z = pack_bf(e[i * 8 + 4] * inv, e[i * 8 + 5] * inv);
                w.w = pack_bf(e[i * 8 + 6] * inv, e[i * 8 + 7] * inv);
                sts128(sb + SM_P + (i * 128 + tid) * 16, w);
            }
            bar_sync(1, 128);
        }
        {
            uint32_t off[4];
#pragma unroll
            for (int i = 0; i < 4; i++)
                off[i] = sb + SM_RING + ((mi >> 1) * 8 + r) * 512 + warp * 128 + (((2 * i + (mi & 1)) ^ r) << 4);
            const uint32_t pmask = t == (g >> 1) ? ((g & 1) ? 0xffff0000u : 0x0000ffffu) : 0u;
            uint32_t* odst = gx->o + ((c & 15) * 8 + (c >> 4)) * 128 + (warp * 2 + (t >> 1)) * 16 + (g >> 1) * 4 +
                             (t & 1) * 2 + (g & 1);
            uint32_t lane2;
            asm volatile("mov.u32 %0, %%laneid;" : "=r"(lane2));
#pragma unroll 1
            for (int pass = 0; pass < 2; pass++) {
                int n = pass * NCH;
                asm volatile("" : "+r"(n));
                float acc[4][4] = {};
                uint32_t psrc = sb + SM_P + t * 32;
                uint32_t va[8][4], vb[8][4] = {};
                uint32_t pt[4] = {};
                uint32_t cur[4];
#pragma unroll
                for (int j = 0; j < 4; j++) cur[j] = off[j] + s * CHUNK;
                uint32_t bar = sb + BAR_FULL + 8 * s, ready = 0;
#pragma unroll 1
                for (int i = n; i > 0; i--) {
                    if (!ready) mbar_wait(bar, ph);
                    const bool wrap = bar == sb + BAR_FULL + 8 * (NS - 1);
                    const uint32_t barn = wrap ? sb + BAR_FULL : bar + 8;
                    ph ^= wrap;
                    const uint4 p0 = lds128(psrc), p1 = lds128(psrc + 16);
#pragma unroll
                    for (int j = 0; j < 2; j++) ldsm4t(va[j], cur[j & 3] + (j >> 2) * 8192);
                    uint32_t tok;
                    asm volatile("{\n.reg .pred p;\nmbarrier.test_wait.parity.shared::cta.b64 p, [%2], %3;\n"
                                 "selp.u32 %0, 1, 0, p;\nselp.u32 %1, %4, %5, p;\n}"
                                 : "=r"(ready), "=r"(tok) : "r"(barn), "r"(ph), "r"(lane), "r"(lane2) : "memory");
#pragma unroll
                    for (int j = 2; j < 8; j++) ldsm4t(va[j], cur[j & 3] + (j >> 2) * 8192);
#pragma unroll
                    for (int j = 0; j < 8; j++) mma(acc[j & 3], vb[j], pt[(j >> 2) * 2], pt[(j >> 2) * 2 + 1]);
#pragma unroll
                    for (int j = 0; j < 8; j++) ldsm4t(vb[j], cur[j & 3] + (2 + (j >> 2)) * 8192);
                    asm volatile("{\n.reg .pred p;\nsetp.eq.u32 p, %1, 0;\n@p mbarrier.arrive.shared::cta.b64 _, [%0];\n}"
                                 ::"r"(bar + 8 * NS), "r"(tok) : "memory");
                    mma(acc[0], va[0], p0.x & pmask, p0.y & pmask);
                    mma(acc[1], va[1], p0.x & pmask, p0.y & pmask);
                    mma(acc[2], va[2], p0.x & pmask, p0.y & pmask);
                    mma(acc[3], va[3], p0.x & pmask, p0.y & pmask);
                    mma(acc[0], va[4], p0.z & pmask, p0.w & pmask);
                    mma(acc[1], va[5], p0.z & pmask, p0.w & pmask);
                    mma(acc[2], va[6], p0.z & pmask, p0.w & pmask);
                    mma(acc[3], va[7], p0.z & pmask, p0.w & pmask);
                    pt[0] = p1.x & pmask;
                    pt[1] = p1.y & pmask;
                    pt[2] = p1.z & pmask;
                    pt[3] = p1.w & pmask;
                    psrc += 128;
                    bar = barn;
                    const uint32_t step = wrap ? -(NS - 1) * CHUNK : CHUNK;
#pragma unroll
                    for (int j = 0; j < 4; j++) cur[j] += step;
                }
#pragma unroll
                for (int j = 0; j < 8; j++) mma(acc[j & 3], vb[j], pt[(j >> 2) * 2], pt[(j >> 2) * 2 + 1]);
                float ev[4], od[4];
#pragma unroll
                for (int T = 0; T < 4; T++) {
                    ev[T] = acc[T][0] + acc[T][3];
                    od[T] = acc[T][1] + acc[T][2];
                }
                ev[0] += __shfl_xor_sync(0xffffffffu, ev[1], 1);
                od[0] += __shfl_xor_sync(0xffffffffu, od[1], 1);
                ev[2] += __shfl_xor_sync(0xffffffffu, ev[3], 1);
                od[2] += __shfl_xor_sync(0xffffffffu, od[3], 1);
                ev[0] += __shfl_xor_sync(0xffffffffu, ev[2], 2);
                od[0] += __shfl_xor_sync(0xffffffffu, od[2], 2);
                const float other = __shfl_xor_sync(0xffffffffu, (g & 1) ? ev[0] : od[0], 4);
                const uint32_t w = (g & 1) ? pack_bf(other, od[0]) : pack_bf(ev[0], other);
                xst32(odst, n ? w : EMPTY);
                __syncwarp();
                if (!n && lane == 0) mbar_arrive(sb + BAR_DRY);
                if (c < 112) {
                    bar_sync(1, 128);
                    if (tid == 0) {
                        const uint32_t on = n ? 0xffffffffu : 0u;
                        mbar_wait(sb + BAR_W0, ~on & 1);
                        l2_prefetch(p.w1 + c * 7168, 14336, on);
                        spin((is_f1 ? W1_DELAY : PF_DELAY) & on);
                        if (!is_f1) {
                            l2_prefetch(p.w2 + fi * 14336, 28672, on);
                            mbar_wait(sb + BAR_E1, ~on & 1);
                            spin(W2_DELAY & on);
                        }
                        tile_loads(sb + (n ? SM_WX : SM_WO + 8192), is_f1 ? &p.map_w1 : &p.map_w2,
                                   is_f1 ? fi * 32 : (fi % 28) * 16, n ? 0 : 1 << 20, is_f1 ? 64 : 224, is_f1 ? 4096 : 7168,
                                   sb + (n ? BAR_W1 : BAR_X), n ? 8 - is_f1 : 1);
                    }
                }
            }
        }
    } else {
        const int ew = warp - 5, et = tid - 160;
        const int r = lane & 7, mi = lane >> 3;
        {
            uint32_t w[7];
#pragma unroll
            for (int i = 0; i < 7; i++)
                asm volatile("ld.global.nc.u32 %0, [%1];" : "=r"(w[i]) : "l"((const uint32_t*)xin + ew * 224 + i * 32 + lane));
            bar_sync(0, NTHREADS);
            layernorm_row(w, sb + SM_XN + ew * 912, lane);
            mbar_wait(sb + BAR_WQ, 0);
            uint32_t a[8][4];
            frags_w448(a, sb + SM_WQ, ew, lane);
            const float2 q = gemv448(a, sb, ew, lane, et);
            if (et < 128) xst32(gx->q + ((et >> 4) * 16 + (c >> 3)) * 128 + (c & 7) * 16 + (et & 15), ~pack_bf(q.x, q.y));
            if (et == 255) mbar_arrive(sb + BAR_QP);
        }
        const int hh = c / 7, jj = c - hh * 7;
        const int cg = fi % 28, half = fi / 28;
        const int ht0 = (c - 112) * 7 + min(ew, 6);
        uint32_t side;
        asm volatile("ld.global.nc.u32 %0, [%1];" : "=r"(side)
                     : "l"(c < 112 ? (is_f1 ? p.b1 + fi * 32 + (et & 15) * 2 : p.b2 + cg * 16 + r * 2)
                           : xin + ((ht0 & 6) + (mi & 1)) * DM + (ht0 >> 3) * 32 + (r & 3) * 8 + (ht0 & 1) * 4 + (r >> 2) * 2));
        uint32_t seen_prog = 0;
#pragma unroll 1
        for (int pass = 0; pass < 2; pass++) {
            uint32_t live = pass;
            asm volatile("" : "+r"(live));
            const uint32_t want = 0u - live, wipe = ~want;
            const int et = pin(tid - 160), ew = et >> 5, lane = et & 31;
            const int g = lane >> 2, t = lane & 3, r = lane & 7, mi = lane >> 3;
            if (et == 0) {
                if (!live) mbar_wait(sb + BAR_Q, 0);
#pragma unroll 1
                for (int it = 0; it < SPIN_LIMIT; it++) {
                    const uint32_t prog = ctl_load(sb + SM_PROG);
                    int total = 0;
                    if (prog == seen_prog) __nanosleep(100);
                    if (prog != seen_prog || prog >= 2 * NCH - 8)
                        asm volatile("ld.relaxed.gpu.global.u32 %0, [%1];" : "=r"(total) : "l"(gx->count + 32) : "memory");
                    if (total >= ALL_CHUNKS - LIFT_LEFT) {
                        ctl_store(sb + SM_DEPTH, NS);
                    } else if (prog != seen_prog) {
                        const int lead = prog * NCTA - total;
                        ctl_store(sb + SM_DEPTH, lead >= LEAD1 ? 1 : lead >= LEAD2 ? 2 : lead >= LEAD2 - 128 ? 3 : lead >= LEAD2 - 256 ? 4 : NS);
                    }
                    seen_prog = prog;
                    if (live ? total >= ALL_CHUNKS - (c < 112 ? TRIG_LEFT : 0) : mbar_test(sb + BAR_DRY, 0)) break;
                }
                tile_loads(sb + SM_WO, &p.map_wo, jj * 64, live ? hh * 256 : 1 << 20, 64, 8192, sb + (live ? BAR_WO : BAR_X + 8),
                           c >= 112 ? 0 : live ? 4 : 1);
            } else if (et == 32 && live) {
                uint32_t seen;
                mbar_wait(sb + BAR_DRY, 0);
                asm volatile("atom.release.gpu.global.add.u32 %0, [%1], 1;" : "=r"(seen) : "l"(gx->count) : "memory");
                int it = 0;
                for (seen++; seen < NCTA && ++it < SPIN_LIMIT;) {
                    __nanosleep(512);
                    asm volatile("ld.relaxed.gpu.global.u32 %0, [%1];" : "=r"(seen) : "l"(gx->count) : "memory");
                }
                asm volatile("ld.acquire.gpu.global.u32 %0, [%1];" : "=r"(seen) : "l"(gx->count) : "memory");
            }
            __syncwarp();
            bar_sync(2, 256);
            if (c >= 112) {
                if (ew < 7) {
                    const bool odd = mi & 1;
                    const int ht = (c - 112) * 7 + ew;
                    float a0, a1;
                    uint32_t* const dst = gx->h + pin((((mi >> 1) * 14 + (ht >> 3)) * 8 + (ht & 6) + (mi & 1)) * 16 + (ht & 1) * 8 + r);
                    Poll<4, 128> in(gx->part + pin(ht * 512 + lane * 4), want, want);
                    spin(R_DELAY & want);
                    in.finish([&] {
                        const uint4 (&v)[4] = in.v;
                        const float f0 = (__uint_as_float(v[0].x) + __uint_as_float(v[1].x)) + (__uint_as_float(v[2].x) + __uint_as_float(v[3].x));
                        const float f1 = (__uint_as_float(v[0].y) + __uint_as_float(v[1].y)) + (__uint_as_float(v[2].y) + __uint_as_float(v[3].y));
                        const float f2 = (__uint_as_float(v[0].z) + __uint_as_float(v[1].z)) + (__uint_as_float(v[2].z) + __uint_as_float(v[3].z));
                        const float f3 = (__uint_as_float(v[0].w) + __uint_as_float(v[1].w)) + (__uint_as_float(v[2].w) + __uint_as_float(v[3].w));
                        a0 = (odd ? f1 : f0) + __shfl_xor_sync(0xffffffffu, odd ? f0 : f1, 8);
                        a1 = (odd ? f3 : f2) + __shfl_xor_sync(0xffffffffu, odd ? f2 : f3, 8);
                    });
                    a0 += __shfl_xor_sync(0xffffffffu, a0, 16);
                    a1 += __shfl_xor_sync(0xffffffffu, a1, 16);
                    xst32(dst, bf2_add(side, pack_bf(a0, a1)) | wipe);
                }
                if (!live) bar_sync(3, 256);
                continue;
            }
            {
                const uint32_t fa = pin(sb + SM_WO + ((ew >> 1) * 64 + (mi >> 1) * 8 + r) * 128 + ((((ew & 1) * 4 + (mi & 1)) ^ r) << 4));
                const uint32_t wb = pin(sb + SM_RED + ((ew >> 1) * 544 + t * 136 + (ew & 1) * 64 + g * 2) * 4);
                const uint32_t rb = pin(sb + SM_RED + ((ew & 3) * 136 + ((ew >> 2) * 32 + (r >> 1) * 8 + mi * 2 + (r & 1)) * 2) * 4);
                uint32_t* const pdst = gx->part + pin((((jj * 8 + ew) * 2 + (lane >> 4)) * 16 + hh) * 32 + (lane & 15) * 2);
                Poll<2, 16> in(gx->o + pin((hh * 8 + g) * 128 + (ew >> 1) * 32 + t * 4), want, want);
                spin_or(O_DELAY & want, sb + BAR_WO + 8 * (ew >> 1));
                in.until(sb + BAR_WO + 8 * (ew >> 1));
                uint32_t a[8][4];
#pragma unroll
                for (int i = 0; i < 4; i++) {
                    const int ks = (i >> 1) + (i & 1) * 2;
                    ldsm4t(a[ks * 2], fa + ks * 2048);
                    ldsm4t(a[ks * 2 + 1], (fa ^ 32) + ks * 2048);
                }
                float acc[2][2][4];
                in.finish([&] {
#pragma unroll
                    for (int i = 0; i < 2; i++) {
                        mma0(acc[i][0], a[i * 4], in.v[i].x, in.v[i].y);
                        mma0(acc[i][1], a[i * 4 + 1], in.v[i].x, in.v[i].y);
                    }
#pragma unroll
                    for (int mt = 0; mt < 2; mt++) {
                        mma(acc[0][mt], a[2 + mt], in.v[0].z, in.v[0].w);
                        mma(acc[1][mt], a[6 + mt], in.v[1].z, in.v[1].w);
                    }
                });
#pragma unroll
                for (int mt = 0; mt < 2; mt++) {
                    sts64f(wb + mt * 128, acc[0][mt][0] + acc[1][mt][0], acc[0][mt][1] + acc[1][mt][1]);
                    sts64f(wb + mt * 128 + 64, acc[0][mt][2] + acc[1][mt][2], acc[0][mt][3] + acc[1][mt][3]);
                }
                bar_sync(2, 256);
                float2 v[4];
#pragma unroll
                for (int w = 0; w < 4; w++) v[w] = lds64f(rb + w * 2176);
                const float s0 = (v[0].x + v[1].x) + (v[2].x + v[3].x);
                const float s1 = (v[0].y + v[1].y) + (v[2].y + v[3].y);
                xst64(pdst, __float_as_uint(s0) | wipe, __float_as_uint(s1) | wipe);
            }
            if (et == 0 && live) mbar_arrive(sb + BAR_E1);
            const uint32_t wbar = sb + BAR_W1 + 8 * ew;
            if (is_f1) {
                constexpr uint32_t ONES = 0x3f803f80u;
                if (ew < 7) {
                    const int b = (et >> 4) & 7, pr = et & 15;
                    const uint32_t fa = pin(sb + SM_WX + (ew * 64 + (mi >> 1) * 8 + r) * 64 + (((mi & 1) ^ (r >> 1)) << 4));
                    const uint32_t wb = pin(sb + SM_RED + (ew * 288 + t * 72 + g) * 4);
                    const uint32_t sw = pin(sb + SM_RED + (ew * 288 + g * 36 + (t == (g >> 1) ? 32 : 34)) * 4);
                    const uint32_t rs = pin(sb + SM_RED + b * 144 + 128), rz = pin(sb + SM_RED + b * 144 + pr * 8);
                    const uint32_t cw = pin(sb + SM_XN + (ew * 32 + g + (t >> 1) * 16 + (t & 1) * 8) * 4), cr = pin(sb + SM_XN + pr * 8);
                    const bool odd = pin(g & 1);
                    uint32_t* const dst = gx->r + pin((((b >> 2) * 56 + fi) * 4 + (b & 3)) * 16 + (pr & 3) * 4 + (pr >> 2));
                    Poll<2, 128> in(gx->h + pin(((fi & 1) * 14 + ew * 2) * 128 + lane * 4), want, want);
                    mbar_wait(wbar, wipe & 1);
                    uint32_t a[8][4];
#pragma unroll
                    for (int ks = 0; ks < 4; ks++) {
                        ldsm4t(a[ks * 2], fa + ks * 1024);
                        ldsm4t(a[ks * 2 + 1], (fa ^ 32) + ks * 1024);
                    }
                    float cs[2][4] = {}, z[2][2][4], st[2][4];
#pragma unroll
                    for (int ks = 0; ks < 4; ks++) {
                        mma(cs[0], a[ks * 2], ONES, ONES);
                        mma(cs[1], a[ks * 2 + 1], ONES, ONES);
                    }
                    sts32f(cw, (t & 1) ? ((t & 2) ? cs[1][2] : cs[0][2]) : ((t & 2) ? cs[1][0] : cs[0][0]));
                    bar_sync(4, 224);
                    float2 cv[7];
#pragma unroll
                    for (int w = 0; w < 7; w++) cv[w] = lds64f(cr + w * 128);
                    const float cs0 = ((cv[0].x + cv[1].x) + (cv[2].x + cv[3].x)) + ((cv[4].x + cv[5].x) + cv[6].x);
                    const float cs1 = ((cv[0].y + cv[1].y) + (cv[2].y + cv[3].y)) + ((cv[4].y + cv[5].y) + cv[6].y);
                    in.finish([&] {
#pragma unroll
                        for (int i = 0; i < 2; i++) {
                            const uint32_t sa[4] = {in.v[i].x, ONES, in.v[i].y, ONES};
                            mma0(z[i][0], a[i * 4], in.v[i].x, in.v[i].y);
                            mma0(z[i][1], a[i * 4 + 1], in.v[i].x, in.v[i].y);
                            mma0(st[i], sa, in.v[i].x, in.v[i].y);
                        }
                    });
#pragma unroll
                    for (int i = 0; i < 2; i++) mma(z[i][0], a[i * 4 + 2], in.v[i].z, in.v[i].w);
#pragma unroll
                    for (int i = 0; i < 2; i++) mma(z[i][1], a[i * 4 + 3], in.v[i].z, in.v[i].w);
#pragma unroll
                    for (int i = 0; i < 2; i++) {
                        const uint32_t sa[4] = {in.v[i].z, ONES, in.v[i].w, ONES};
                        mma(st[i], sa, in.v[i].z, in.v[i].w);
                    }
#pragma unroll
                    for (int mt = 0; mt < 2; mt++) {
                        sts32f(wb + mt * 64, z[0][mt][0] + z[1][mt][0]);
                        sts32f(wb + mt * 64 + 144, z[0][mt][1] + z[1][mt][1]);
                        sts32f(wb + mt * 64 + 32, z[0][mt][2] + z[1][mt][2]);
                        sts32f(wb + mt * 64 + 176, z[0][mt][3] + z[1][mt][3]);
                    }
                    sts64f(sw, odd ? st[0][3] + st[1][3] : st[0][2] + st[1][2], odd ? st[0][1] + st[1][1] : st[0][0] + st[1][0]);
                    bar_sync(4, 224);
                    if (ew < 4) {
                        float2 sv[7], zv[7];
#pragma unroll
                        for (int w = 0; w < 7; w++) sv[w] = lds64f(rs + w * 1152);
#pragma unroll
                        for (int w = 0; w < 7; w++) zv[w] = lds64f(rz + w * 1152);
                        const float mu = (((sv[0].x + sv[1].x) + (sv[2].x + sv[3].x)) + ((sv[4].x + sv[5].x) + sv[6].x)) * (1.f / DM);
                        const float sq = ((sv[0].y + sv[1].y) + (sv[2].y + sv[3].y)) + ((sv[4].y + sv[5].y) + sv[6].y);
                        const float inv = inv_std(bf_round(fmaxf(fmaf(sq, 1.f / DM, -mu * mu), 0.f)));
                        const float mean = bf_round(mu);
                        const float z0 = ((zv[0].x + zv[1].x) + (zv[2].x + zv[3].x)) + ((zv[4].x + zv[5].x) + zv[6].x);
                        const float z1 = ((zv[0].y + zv[1].y) + (zv[2].y + zv[3].y)) + ((zv[4].y + zv[5].y) + zv[6].y);
                        const uint32_t u = pack_bf(fmaf(-mean, cs0, z0) * inv, fmaf(-mean, cs1, z1) * inv);
                        xst32(dst, bf2_relu_sq(bf2_add(u, side)) | wipe);
                    }
                    if (c == 0 && et == 128 && live) {
                        xst32(gx->count, 0);
                        xst32(gx->count + 32, 0);
                    }
                }
            } else {
                const uint32_t fa = pin(sb + SM_WX + (ew * 224 + (mi >> 1) * 8 + r) * 32 + (((mi & 1) ^ (r >> 2)) << 4));
                const uint32_t wb = pin(sb + SM_XN + (ew * 160 + (t & 1) * 80 + (g >> 1) * 4 + (t >> 1) * 2 + (g & 1)) * 4);
                const uint32_t rb = pin(sb + SM_XN + (mi * 40 + r * 4) * 4);
                const bool upper = pin(t >> 1), first = pin(ew == 0);
                uint32_t* const dst = (live ? (uint32_t*)p.out : gx->sink) + pin((half * 4 + mi) * 224 + cg * 8 + r);
                Poll<4, 128, true> in(gx->r + pin((half * 56 + ew * 7) * 64 + lane * 4), want, lane < 16 ? want : 0u,
                                      gx->h + pin((((fi & 1) * 14 + (cg >> 1)) * 8 + half * 4 + mi) * 16 + (r & 3) * 4 +
                                                  (cg & 1) * 2 + (r >> 2)),
                                      ew == 0 ? want : 0u);
                mbar_wait(wbar, wipe & 1);
                uint32_t a[14][4];
#pragma unroll
                for (int ks = 0; ks < 14; ks++) ldsm4t(a[ks], fa + ks * 512);
                float acc[4][4];
                const auto step = [&](int i) {
                    mma(acc[0], a[4 * i], in.v[i].x, in.v[i].y);
                    mma(acc[1], a[4 * i + 1], in.v[i].z, in.v[i].w);
                    if (i < 3) {
                        mma(acc[2], a[4 * i + 2], in.v[i].x, in.v[i].y);
                        mma(acc[3], a[4 * i + 3], in.v[i].z, in.v[i].w);
                    }
                };
                in.finish([&] {
                    mma0(acc[0], a[0], in.v[0].x, in.v[0].y);
                    mma0(acc[1], a[1], in.v[0].z, in.v[0].w);
                    mma0(acc[2], a[2], in.v[0].x, in.v[0].y);
                    mma0(acc[3], a[3], in.v[0].z, in.v[0].w);
                    step(1);
                });
                step(2);
                step(3);
                sts32f(wb, upper ? acc[2][0] + acc[3][0] : acc[0][0] + acc[1][0]);
                sts32f(wb + 160, upper ? acc[2][1] + acc[3][1] : acc[0][1] + acc[1][1]);
                sts32f(wb + 64, upper ? acc[2][2] + acc[3][2] : acc[0][2] + acc[1][2]);
                sts32f(wb + 224, upper ? acc[2][3] + acc[3][3] : acc[0][3] + acc[1][3]);
                bar_sync(2, 256);
                if (first) {
                    float x[8], y[8];
#pragma unroll
                    for (int w = 0; w < 8; w++) {
                        const uint4 q = lds128(rb + w * 640);
                        x[w] = __uint_as_float(q.x) + __uint_as_float(q.z);
                        y[w] = __uint_as_float(q.y) + __uint_as_float(q.w);
                    }
                    const float s0 = ((x[0] + x[1]) + (x[2] + x[3])) + ((x[4] + x[5]) + (x[6] + x[7]));
                    const float s1 = ((y[0] + y[1]) + (y[2] + y[3])) + ((y[4] + y[5]) + (y[6] + y[7]));
                    *dst = bf2_add(in.word, bf2_add(pack_bf(s0, s1), side));
                }
                exit_if(live);
            }
            if (!live) bar_sync(3, 256);
        }
    }
}

using EncodeFn = CUresult (*)(CUtensorMap*, CUtensorMapDataType, cuuint32_t, void*, const cuuint64_t*, const cuuint64_t*,
                              const cuuint32_t*, const cuuint32_t*, CUtensorMapInterleave, CUtensorMapSwizzle,
                              CUtensorMapL2promotion, CUtensorMapFloatOOBfill);

void encode_map(EncodeFn fn, CUtensorMap* map, const void* base, int rows, int cols, int box_rows, int box_cols,
                CUtensorMapSwizzle swizzle) {
    const cuuint64_t dims[2] = {(cuuint64_t)cols, (cuuint64_t)rows};
    const cuuint64_t strides[1] = {(cuuint64_t)cols * 2};
    const cuuint32_t box[2] = {(cuuint32_t)box_cols, (cuuint32_t)box_rows};
    const cuuint32_t steps[2] = {1, 1};
    fn(map, CU_TENSOR_MAP_DATA_TYPE_BFLOAT16, 2, const_cast<void*>(base), dims, strides, box, steps,
       CU_TENSOR_MAP_INTERLEAVE_NONE, swizzle, CU_TENSOR_MAP_L2_PROMOTION_L2_128B, CU_TENSOR_MAP_FLOAT_OOB_FILL_NONE);
}

}

extern "C" void kernel_launch(void* const* d_in, const int* in_sizes, int n_in, void* d_out, int out_size) {
    (void)in_sizes; (void)n_in; (void)out_size;
    Params p;
    p.w1 = (const __nv_bfloat16*)d_in[6];
    p.b1 = (const __nv_bfloat16*)d_in[7];
    p.w2 = (const __nv_bfloat16*)d_in[8];
    p.b2 = (const __nv_bfloat16*)d_in[9];
    p.out = (__nv_bfloat16*)d_out;
    Exchange* xch = nullptr;
    cudaGetSymbolAddress((void**)&xch, g_x);
    void* fn = nullptr;
    cudaDriverEntryPointQueryResult found;
    cudaGetDriverEntryPoint("cuTensorMapEncodeTiled", &fn, cudaEnableDefault, &found);
    encode_map((EncodeFn)fn, &p.map_wo, d_in[4], NH * DH, DM, 64, 64, CU_TENSOR_MAP_SWIZZLE_128B);
    encode_map((EncodeFn)fn, &p.map_w1, p.w1, DM, FF, 64, 32, CU_TENSOR_MAP_SWIZZLE_64B);
    encode_map((EncodeFn)fn, &p.map_w2, p.w2, FF, DM, 224, 16, CU_TENSOR_MAP_SWIZZLE_32B);
    cudaFuncSetAttribute(fused_decode_kernel, cudaFuncAttributeMaxDynamicSharedMemorySize, SM_TOTAL);
    fused_decode_kernel<<<NCTA, NTHREADS, SM_TOTAL>>>((const __nv_bfloat16*)d_in[3], (const __nv_bfloat16*)d_in[0],
                                                      (const char*)d_in[1], (const char*)d_in[2], xch, p);
}
```

```cpp
#include <cuda.h>
#include <cuda_runtime.h>
#include <cuda_bf16.h>
#include <stdint.h>

namespace {

constexpr int DM = 448, NH = 16, SK = 4096, DH = 256, FF = 1792;
constexpr int NCTA = 128;
constexpr int CHUNK = 32768;
constexpr int NCH = SK / 64;
constexpr int NS = 5;
constexpr int ALL_CHUNKS = NCTA * 2 * NCH;
constexpr int LEAD1 = 128;
constexpr int LEAD2 = -128;
constexpr int LIFT_LEFT = 370;
constexpr int TRIG_LEFT = 220;
constexpr int K1_DELAY = 1000;
constexpr int Q_SLEEP = 100;
constexpr int W1_DELAY = 600;
constexpr int PF_DELAY = 500;
constexpr int W2_DELAY = 600;
constexpr int ROT = 32;
constexpr int R_DELAY = 200;
constexpr int O_DELAY = 1600;
constexpr int NTHREADS = 13 * 32;
constexpr int SPIN_LIMIT = 1 << 18;
constexpr int WAIT_LIMIT = 1 << 15;

constexpr int SM_RING = 0;
constexpr int SM_WX = 0;
constexpr int SM_WQ = NS * CHUNK;
constexpr int SM_WO = SM_WQ;
constexpr int SM_P = SM_WQ + 32768;
constexpr int SM_RED = SM_P + 8192;
constexpr int SM_XN = SM_RED + 4 * 544 * 4;
constexpr int SM_Q = SM_XN + 8 * 456 * 2;
constexpr int SM_STAT = SM_Q + 512;
constexpr int SM_PROG = SM_STAT + 32, SM_DEPTH = SM_STAT + 36;
constexpr int SM_BAR = SM_STAT + 64;
constexpr int BAR_FULL = SM_BAR, BAR_EMPTY = BAR_FULL + 8 * NS, BAR_WO = BAR_EMPTY + 8 * NS, BAR_DRY = BAR_WO + 32,
              BAR_WQ = BAR_DRY + 8, BAR_Q = BAR_WQ + 8, BAR_W0 = BAR_WO + 24, BAR_E1 = BAR_Q + 8, BAR_X = BAR_E1 + 8,
              BAR_QP = BAR_X + 16, BAR_W1 = BAR_QP + 8;
constexpr int SM_TOTAL = BAR_W1 + 64;
static_assert(SM_TOTAL <= 232448, "shared memory budget");

struct Exchange {
    uint32_t q[NCTA * 128];
    uint32_t o[NH * 8 * 128];
    uint32_t part[14 * 8 * 16 * 32];
    uint32_t h[2 * 14 * 8 * 16];
    uint32_t r[2 * 56 * 4 * 16];
    uint32_t count[64];
    uint32_t sink[8 * 224];
};
__device__ __align__(128) Exchange g_x;

__device__ __forceinline__ void mbar_init(uint32_t bar, uint32_t count) {
    asm volatile("mbarrier.init.shared::cta.b64 [%0], %1;" ::"r"(bar), "r"(count) : "memory");
}
__device__ __forceinline__ void mbar_arrive(uint32_t bar) {
    asm volatile("mbarrier.arrive.shared::cta.b64 _, [%0];" ::"r"(bar) : "memory");
}
__device__ __forceinline__ void mbar_expect_tx(uint32_t bar, uint32_t bytes) {
    asm volatile("mbarrier.arrive.expect_tx.shared::cta.b64 _, [%0], %1;" ::"r"(bar), "r"(bytes) : "memory");
}
__device__ __forceinline__ void mbar_wait(uint32_t bar, uint32_t parity) {
    asm volatile("{\n.reg .pred p, q;\n.reg .u32 n;\nmov.u32 n, %2;\n"
                 "RETRY:\nsub.u32 n, n, 1;\nsetp.ne.u32 q, n, 0;\n"
                 "mbarrier.try_wait.parity.shared::cta.b64 p, [%0], %1;\nand.pred q, q, !p;\n@q bra RETRY;\n}"
                 ::"r"(bar), "r"(parity), "n"(WAIT_LIMIT) : "memory");
}
__device__ __forceinline__ uint32_t mbar_test(uint32_t bar, uint32_t parity) {
    uint32_t done;
    asm volatile("{\n.reg .pred p;\nmbarrier.test_wait.parity.shared::cta.b64 p, [%1], %2;\nselp.u32 %0, 1, 0, p;\n}"
                 : "=r"(done) : "r"(bar), "r"(parity) : "memory");
    return done;
}
__device__ __forceinline__ void exit_if(uint32_t on) {
    asm volatile("{\n.reg .pred p;\nsetp.ne.u32 p, %0, 0;\n@p exit;\n}" ::"r"(on) : "memory");
}
__device__ __forceinline__ void spin(uint32_t cycles) {
    const uint32_t t0 = (uint32_t)clock();
    do {
    } while ((uint32_t)clock() - t0 < cycles);
}
__device__ __forceinline__ void spin_or(uint32_t cycles, uint32_t bar) {
    const uint32_t t0 = (uint32_t)clock();
    do {
    } while (!mbar_test(bar, 0) && (uint32_t)clock() - t0 < cycles);
}
__device__ __forceinline__ void l2_prefetch(const void* src, uint32_t bytes, uint32_t on) {
    asm volatile("{\n.reg .pred p;\nsetp.ne.u32 p, %2, 0;\n@p cp.async.bulk.prefetch.L2.global [%0], %1;\n}"
                 ::"l"(src), "r"(bytes), "r"(on) : "memory");
}
__device__ __forceinline__ void bulk_load(uint32_t dst, const void* src, uint32_t bytes, uint32_t bar, uint64_t pol) {
    asm volatile("cp.async.bulk.shared::cluster.global.mbarrier::complete_tx::bytes.L2::cache_hint [%0], [%1], %2, [%3], %4;"
                 ::"r"(dst), "l"(src), "r"(bytes), "r"(bar), "l"(pol) : "memory");
}
__device__ __forceinline__ void tile_loads(uint32_t dst, const CUtensorMap* map, int col, int row, int rows, uint32_t bytes,
                                           uint32_t bar, int n) {
#pragma unroll 1
    for (int i = 0; i < n; i++, dst += bytes, row += rows, bar += 8) {
        mbar_expect_tx(bar, bytes);
        asm volatile("cp.async.bulk.tensor.2d.shared::cluster.global.mbarrier::complete_tx::bytes [%0], [%1, {%2, %3}], [%4];"
                     ::"r"(dst), "l"(map), "r"(col), "r"(row), "r"(bar) : "memory");
    }
}
__device__ __forceinline__ void bar_sync(int id, int n) { asm volatile("bar.sync %0, %1;" ::"r"(id), "r"(n) : "memory"); }

__device__ __forceinline__ void ldsm4(uint32_t (&r)[4], uint32_t a) {
    asm volatile("ldmatrix.sync.aligned.m8n8.x4.shared.b16 {%0,%1,%2,%3}, [%4];"
                 : "=r"(r[0]), "=r"(r[1]), "=r"(r[2]), "=r"(r[3]) : "r"(a) : "memory");
}
__device__ __forceinline__ void ldsm4t(uint32_t (&r)[4], uint32_t a) {
    asm volatile("ldmatrix.sync.aligned.m8n8.x4.trans.shared.b16 {%0,%1,%2,%3}, [%4];"
                 : "=r"(r[0]), "=r"(r[1]), "=r"(r[2]), "=r"(r[3]) : "r"(a) : "memory");
}
__device__ __forceinline__ void mma(float (&c)[4], const uint32_t (&a)[4], uint32_t b0, uint32_t b1) {
    asm volatile("mma.sync.aligned.m16n8k16.row.col.f32.bf16.bf16.f32 {%0,%1,%2,%3}, {%4,%5,%6,%7}, {%8,%9}, {%0,%1,%2,%3};"
                 : "+f"(c[0]), "+f"(c[1]), "+f"(c[2]), "+f"(c[3])
                 : "r"(a[0]), "r"(a[1]), "r"(a[2]), "r"(a[3]), "r"(b0), "r"(b1));
}
__device__ __forceinline__ void mma0(float (&c)[4], const uint32_t (&a)[4], uint32_t b0, uint32_t b1) {
    asm volatile("mma.sync.aligned.m16n8k16.row.col.f32.bf16.bf16.f32 {%0,%1,%2,%3}, {%4,%5,%6,%7}, {%8,%9}, {%10,%10,%10,%10};"
                 : "=f"(c[0]), "=f"(c[1]), "=f"(c[2]), "=f"(c[3])
                 : "r"(a[0]), "r"(a[1]), "r"(a[2]), "r"(a[3]), "r"(b0), "r"(b1), "f"(0.f));
}
__device__ __forceinline__ uint32_t lds32(uint32_t a) {
    uint32_t v;
    asm volatile("ld.shared.u32 %0, [%1];" : "=r"(v) : "r"(a) : "memory");
    return v;
}
__device__ __forceinline__ uint32_t ctl_load(uint32_t a) {
    uint32_t v;
    asm volatile("ld.volatile.shared.u32 %0, [%1];" : "=r"(v) : "r"(a) : "memory");
    return v;
}
__device__ __forceinline__ void ctl_store(uint32_t a, uint32_t v) {
    asm volatile("st.volatile.shared.u32 [%0], %1;" ::"r"(a), "r"(v) : "memory");
}
__device__ __forceinline__ float2 lds64f(uint32_t a) {
    float2 v;
    asm volatile("ld.shared.v2.f32 {%0,%1}, [%2];" : "=f"(v.x), "=f"(v.y) : "r"(a) : "memory");
    return v;
}
__device__ __forceinline__ uint4 lds128(uint32_t a) {
    uint4 v;
    asm volatile("ld.shared.v4.u32 {%0,%1,%2,%3}, [%4];" : "=r"(v.x), "=r"(v.y), "=r"(v.z), "=r"(v.w) : "r"(a) : "memory");
    return v;
}
__device__ __forceinline__ void sts16(uint32_t a, uint32_t v) {
    asm volatile("st.shared.u16 [%0], %1;" ::"r"(a), "h"((unsigned short)v) : "memory");
}
__device__ __forceinline__ void sts32(uint32_t a, uint32_t v) {
    asm volatile("st.shared.u32 [%0], %1;" ::"r"(a), "r"(v) : "memory");
}
__device__ __forceinline__ void sts32f(uint32_t a, float v) {
    asm volatile("st.shared.f32 [%0], %1;" ::"r"(a), "f"(v) : "memory");
}
__device__ __forceinline__ void sts64f(uint32_t a, float x, float y) {
    asm volatile("st.shared.v2.f32 [%0], {%1,%2};" ::"r"(a), "f"(x), "f"(y) : "memory");
}
__device__ __forceinline__ void sts128(uint32_t a, uint4 v) {
    asm volatile("st.shared.v4.u32 [%0], {%1,%2,%3,%4};" ::"r"(a), "r"(v.x), "r"(v.y), "r"(v.z), "r"(v.w) : "memory");
}

constexpr uint32_t EMPTY = 0xffffffffu;
__device__ __forceinline__ void xld32(uint32_t& v, const uint32_t* p, uint32_t empty) {
    asm volatile("{\n.reg .pred p;\nsetp.eq.u32 p, %0, %2;\n@p ld.relaxed.gpu.global.u32 %0, [%1];\n}"
                 : "+r"(v) : "l"(p), "r"(empty) : "memory");
}
__device__ __forceinline__ void xld128(uint4& v, const uint32_t* p, uint32_t top) {
    asm volatile("{\n.reg .pred p;\nsetp.eq.u32 p, %5, 0xffffffff;\n@p ld.relaxed.gpu.global.v4.u32 {%0,%1,%2,%3}, [%4];\n}"
                 : "+r"(v.x), "+r"(v.y), "+r"(v.z), "+r"(v.w) : "l"(p), "r"(top) : "memory");
}
__device__ __forceinline__ void xst32(uint32_t* p, uint32_t v) {
    asm volatile("st.relaxed.gpu.global.u32 [%0], %1;" ::"l"(p), "r"(v) : "memory");
}
__device__ __forceinline__ void xst64(uint32_t* p, uint32_t a, uint32_t b) {
    asm volatile("st.relaxed.gpu.global.v2.u32 [%0], {%1,%2};" ::"l"(p), "r"(a), "r"(b) : "memory");
}
__device__ __forceinline__ uint32_t top_word(const uint4& v) { return max(__vimax3_u32(v.x, v.y, v.z), v.w); }
template <int N, int STRIDE, bool WORD = false>
struct Poll {
    uint4 v[N];
    uint32_t top[N], word, want;
    const uint32_t *src, *wsrc;
    int left;
    __device__ __forceinline__ Poll(const uint32_t* s, uint32_t init, uint32_t init_last, const uint32_t* ws = nullptr,
                                    uint32_t init_word = 0)
        : word(init_word), want(init), src(s), wsrc(ws), left(init ? SPIN_LIMIT : 2) {
#pragma unroll
        for (int i = 0; i < N; i++) {
            top[i] = i == N - 1 ? init_last : init;
            v[i] = make_uint4(top[i], top[i], top[i], top[i]);
        }
    }
    __device__ __forceinline__ void issue() {
#pragma unroll
        for (int i = 0; i < N; i++) xld128(v[i], src + i * STRIDE, top[i]);
        if (WORD) xld32(word, wsrc, EMPTY);
        left--;
    }
    __device__ __forceinline__ bool missing() {
        uint32_t m = WORD ? word : 0;
#pragma unroll
        for (int i = 0; i < N; i++) {
            top[i] = top_word(v[i]);
            m = max(m, top[i]);
        }
        return __any_sync(0xffffffffu, m == want && left > 0);
    }
    __device__ __forceinline__ void until(uint32_t bar) {
#pragma unroll 1
        while (!mbar_test(bar, 0)) {
            issue();
            if (!missing()) break;
        }
        mbar_wait(bar, ~want & 1);
    }
    template <class F>
    __device__ __forceinline__ void finish(F use) {
        bool again;
#pragma unroll 1
        do {
            issue();
            again = missing();
            use();
        } while (again);
    }
};
__device__ __forceinline__ uint32_t pin(uint32_t v) {
    asm volatile("shfl.sync.bfly.b32 %0, %0, 0, 0x1f, 0xffffffff;" : "+r"(v));
    return v;
}
__device__ __forceinline__ uint32_t bf2_add(uint32_t a, uint32_t b) {
    uint32_t r;
    asm("add.rn.bf16x2 %0, %1, %2;" : "=r"(r) : "r"(a), "r"(b));
    return r;
}
__device__ __forceinline__ uint32_t bf2_relu_sq(uint32_t a) {
    uint32_t r;
    asm("{\n.reg .b32 m;\nmax.bf16x2 m, %1, %2;\nmul.rn.bf16x2 %0, m, m;\n}" : "=r"(r) : "r"(a), "r"(0));
    return r;
}

__device__ __forceinline__ uint32_t pack_bf(float lo, float hi) {
    uint32_t r;
    asm("cvt.rn.bf16x2.f32 %0, %1, %2;" : "=r"(r) : "f"(hi), "f"(lo));
    return r;
}
__device__ __forceinline__ float bf_round(float v) { return __uint_as_float(pack_bf(0.f, v)); }
__device__ __forceinline__ float bf_lo(uint32_t w) { return __uint_as_float(w << 16); }
__device__ __forceinline__ float bf_hi(uint32_t w) { return __uint_as_float(w & 0xffff0000u); }

__device__ __forceinline__ float inv_std(float var) {
    float sd, inv;
    asm("sqrt.approx.ftz.f32 %0, %1;" : "=f"(sd) : "f"(bf_round(var + 1e-5f)));
    asm("rcp.approx.ftz.f32 %0, %1;" : "=f"(inv) : "f"(bf_round(sd)));
    return inv;
}

__device__ __forceinline__ void layernorm_row(const uint32_t (&w)[7], uint32_t dst, int lane) {
    const float shift = bf_lo(__shfl_sync(0xffffffffu, w[0], 0));
    float s = 0.f, ss = 0.f;
#pragma unroll
    for (int i = 0; i < 7; i++) {
        const float a = bf_lo(w[i]) - shift, b = bf_hi(w[i]) - shift;
        s += a + b;
        ss = fmaf(a, a, fmaf(b, b, ss));
    }
#pragma unroll
    for (int o = 16; o; o >>= 1) {
        s += __shfl_xor_sync(0xffffffffu, s, o);
        ss += __shfl_xor_sync(0xffffffffu, ss, o);
    }
    const float md = s * (1.f / DM);
    const float mean = bf_round(shift + md);
    const float inv = inv_std(bf_round(fmaxf(ss * (1.f / DM) - md * md, 0.f)));
#pragma unroll
    for (int i = 0; i < 7; i++) {
        const float a = bf_round(bf_lo(w[i]) - mean) * inv, b = bf_round(bf_hi(w[i]) - mean) * inv;
        sts32(dst + (i * 32 + lane) * 4, pack_bf(a, b));
    }
}

__device__ __forceinline__ void frags_w448(uint32_t (&a)[8][4], uint32_t src, int ew, int lane) {
    const int r = lane & 7, mi = lane >> 3;
    const uint32_t base = src + ((ew < 7 ? ew : 0) * 64 + (mi >> 1) * 8 + r) * 64;
#pragma unroll
    for (int ks = 0; ks < 4; ks++)
#pragma unroll
        for (int mt = 0; mt < 2; mt++)
            ldsm4t(a[ks * 2 + mt], base + ks * 1024 + (((2 * mt + (mi & 1)) ^ (r >> 1)) << 4));
}
__device__ __forceinline__ float2 gemv448(const uint32_t (&a)[8][4], uint32_t sb, int ew, int lane, int et) {
    const int g = lane >> 2, t = lane & 3;
    bar_sync(2, 256);
    if (ew < 7) {
        float c[4][4] = {};
        const uint32_t xb = sb + SM_XN + (g * 228 + ew * 32 + t) * 4;
#pragma unroll
        for (int ks = 0; ks < 4; ks++) {
            const uint32_t b0 = lds32(xb + ks * 32), b1 = lds32(xb + ks * 32 + 16);
            mma(c[(ks & 1) * 2], a[ks * 2], b0, b1);
            mma(c[(ks & 1) * 2 + 1], a[ks * 2 + 1], b0, b1);
        }
        const uint32_t rb = sb + SM_RED + (ew * 288 + t * 72 + g) * 4;
#pragma unroll
        for (int mt = 0; mt < 2; mt++) {
            sts32f(rb + mt * 64, c[mt][0] + c[2 + mt][0]);
            sts32f(rb + mt * 64 + 144, c[mt][1] + c[2 + mt][1]);
            sts32f(rb + mt * 64 + 32, c[mt][2] + c[2 + mt][2]);
            sts32f(rb + mt * 64 + 176, c[mt][3] + c[2 + mt][3]);
        }
    }
    bar_sync(2, 256);
    float2 acc = make_float2(0.f, 0.f);
    if (et < 128) {
        const uint32_t rb = sb + SM_RED + ((et >> 4) * 36 + (et & 15) * 2) * 4;
#pragma unroll
        for (int w = 0; w < 7; w++) {
            const float2 v = lds64f(rb + w * 1152);
            acc.x += v.x;
            acc.y += v.y;
        }
    }
    return acc;
}

struct Params {
    const __nv_bfloat16 *w1, *b1, *w2, *b2;
    __nv_bfloat16* out;
    alignas(64) CUtensorMap map_wo, map_w1, map_w2;
};

__global__ void __launch_bounds__(NTHREADS, 1)
fused_decode_kernel(const __nv_bfloat16* const wq, const __nv_bfloat16* const xin, const char* const kc, const char* const vc,
                    Exchange* const gx, const __grid_constant__ Params p) {
    extern __shared__ __align__(1024) unsigned char smem[];
    const uint32_t sb = (uint32_t)__cvta_generic_to_shared(smem);
    const int tid = threadIdx.x, warp = tid >> 5, lane = tid & 31;
    const int c = blockIdx.x;
    const char* kbase = kc + (size_t)c * (SK * DH * 2);
    const char* vbase = vc + (size_t)c * (SK * DH * 2);

    const int rot = (c * ROT) & (NCH - 1);
    const bool is_f1 = !(c & 1);
    const int fi = c >> 1;

    asm volatile("{\n.reg .pred p;\n.reg .b32 w;\n.reg .b64 a;\nmov.u32 w, %%ctaid.x;\nmad.wide.u32 a, w, 28672, %0;\n"
                 "setp.eq.u32 p, %1, 128;\n@p cp.async.bulk.prefetch.L2.global [a], 28672;\n}"
                 ::"l"(wq), "r"(tid) : "memory");
    uint64_t pol = 0;
    if (tid == 128) {
        mbar_init(sb + BAR_FULL, 1);
        asm volatile("fence.mbarrier_init.release.cluster;" ::: "memory");
        asm volatile("createpolicy.fractional.L2::evict_first.b64 %0, 1.0;" : "=l"(pol));
        mbar_expect_tx(sb + BAR_FULL, CHUNK);
        bulk_load(sb + SM_RING, kbase + rot * CHUNK, CHUNK, sb + BAR_FULL, pol);
    }
    if (warp == 4) {
        if (lane == 0) {
#pragma unroll
            for (int s = 0; s < NS; s++) {
                if (s) mbar_init(sb + BAR_FULL + 8 * s, 1);
                mbar_init(sb + BAR_EMPTY + 8 * s, 4);
            }
#pragma unroll
            for (int w = 0; w < 8; w++) {
                if (w < 4) mbar_init(sb + BAR_WO + 8 * w, 1);
                mbar_init(sb + BAR_W1 + 8 * w, 1);
            }
            mbar_init(sb + BAR_DRY, 4);
            mbar_init(sb + BAR_WQ, 128);
            mbar_init(sb + BAR_Q, 1);
            mbar_init(sb + BAR_QP, 1);
            mbar_init(sb + BAR_E1, 1);
            mbar_init(sb + BAR_X, 1);
            mbar_init(sb + BAR_X + 8, 1);
            ctl_store(sb + SM_PROG, 0);
            ctl_store(sb + SM_DEPTH, 2);
            asm volatile("fence.mbarrier_init.release.cluster;" ::: "memory");
        }
        __syncwarp();
        asm volatile("bar.arrive 0, %0;" ::"n"(NTHREADS) : "memory");
        if (lane == 0) {
            spin_or(K1_DELAY, sb + BAR_WQ);
            int s = 1, sl = 0, landed = 0;
            uint32_t ph = 1, phl = 0;
#pragma unroll 1
            for (int i = 1; i <= 2 * NCH; i++) {
                const char* src = (i < NCH ? kbase : vbase) + ((i + rot) & (NCH - 1)) * CHUNK;
                for (int it = 0; landed < (i < 2 * NCH ? i + 1 - (int)ctl_load(sb + SM_DEPTH) : i); it++) {
                    if (mbar_test(sb + BAR_FULL + 8 * sl, phl) || it >= 4 * SPIN_LIMIT) {
                        asm volatile("red.relaxed.gpu.global.add.u32 [%0], 1;" ::"l"(gx->count + 32) : "memory");
                        ctl_store(sb + SM_PROG, ++landed);
                        if (++sl == NS) { sl = 0; phl ^= 1; }
                    } else {
                        __nanosleep(20);
                    }
                }
                if (i == 2 * NCH) break;
                mbar_wait(sb + BAR_EMPTY + 8 * s, ph);
                mbar_expect_tx(sb + BAR_FULL + 8 * s, CHUNK);
                bulk_load(sb + SM_RING + s * CHUNK, src, CHUNK, sb + BAR_FULL + 8 * s, pol);
                if (++s == NS) { s = 0; ph ^= 1; }
            }
        }
    } else if (warp < 4) {
        const int g = lane >> 2, t = lane & 3, r = lane & 7, mi = lane >> 3;
        {
            const int row = tid >> 2, ch = tid & 3;
            const uint32_t dst = sb + SM_WQ + row * 64 + ((ch ^ ((row >> 1) & 3)) << 4);
            const __nv_bfloat16* src = wq + row * (NH * DH) + c * 32 + ch * 8;
#pragma unroll
            for (int i = 0; i < 14; i++)
                asm volatile("cp.async.cg.shared.global [%0], [%1], 16;" ::"r"(dst + i * 2048), "l"(src + i * 32 * (NH * DH)) : "memory");
            uint32_t* slot = gx->q + c * 128 + tid;
            uint32_t w = 0;
#pragma unroll 1
            for (int it = 0; it < SPIN_LIMIT; it++) {
                xld32(w, slot, 0);
                if (it == 0) {
                    bar_sync(0, NTHREADS);
                    asm volatile("cp.async.mbarrier.arrive.noinc.shared::cta.b64 [%0];" ::"r"(sb + BAR_WQ) : "memory");
                }
                if (!__any_sync(0xffffffffu, w == 0)) break;
                __nanosleep(Q_SLEEP);
            }
            xst32(slot, 0);
            sts32(sb + SM_Q + tid * 4, ~w);
        }
        bar_sync(1, 128);
        if (tid == 0) mbar_arrive(sb + BAR_Q);
        int s = 0;
        uint32_t ph = 0;
        float rmax = -INFINITY;
        {
            uint32_t qf[32];
#pragma unroll
            for (int i = 0; i < 32; i++) qf[i] = lds32(sb + SM_Q + ((i ^ g) * 4 + t) * 4);
            uint32_t off[4];
#pragma unroll
            for (int i = 0; i < 4; i++)
                off[i] = sb + SM_RING + (warp * 16 + (mi & 1) * 8 + r) * 512 + (((2 * i + (mi >> 1)) ^ r) << 4);
            const bool owner = t == (g >> 1);
            uint32_t pdst = sb + SM_P + (t * 16 + warp * 4 + (g & 1)) * 2;
#pragma unroll 1
            for (int i = 0; i < NCH; i++) {
                mbar_wait(sb + BAR_FULL + 8 * s, ph);
                float acc[4][4] = {};
#pragma unroll
                for (int ks = 0; ks < 16; ks++) {
                    uint32_t a[4];
                    ldsm4(a, off[ks & 3] + s * CHUNK + (ks >> 2) * 128);
                    mma(acc[ks & 3], a, qf[2 * ks], qf[2 * ks + 1]);
                }
                __syncwarp();
                if (lane == 0) mbar_arrive(sb + BAR_EMPTY + 8 * s);
                float v[4];
#pragma unroll
                for (int e = 0; e < 4; e++) v[e] = (acc[0][e] + acc[1][e]) + (acc[2][e] + acc[3][e]);
                const float lo = (g & 1) ? v[1] : v[0], hi = (g & 1) ? v[3] : v[2];
                const uint32_t sc = pack_bf(bf_round(lo) * 0.0625f, bf_round(hi) * 0.0625f);
                if (owner) {
                    sts16(pdst, sc & 0xffffu);
                    sts16(pdst + 4, sc >> 16);
                    rmax = fmaxf(rmax, fmaxf(bf_lo(sc), bf_hi(sc)));
                }
                pdst += 128;
                if (++s == NS) { s = 0; ph ^= 1; }
            }
        }
        mbar_wait(sb + BAR_QP, 0);
        asm volatile("fence.proxy.async.shared::cta;" ::: "memory");
        {
#pragma unroll
            for (int o = 16; o; o >>= 1) rmax = fmaxf(rmax, __shfl_xor_sync(0xffffffffu, rmax, o));
            if (lane == 0) sts32f(sb + SM_STAT + warp * 4, rmax);
            bar_sync(1, 128);
            const uint4 mx = lds128(sb + SM_STAT);
            const float m = fmaxf(fmaxf(__uint_as_float(mx.x), __uint_as_float(mx.y)),
                                  fmaxf(__uint_as_float(mx.z), __uint_as_float(mx.w)));
            float e[32];
            float sum = 0.f;
#pragma unroll
            for (int i = 0; i < 4; i++) {
                const uint4 w = lds128(sb + SM_P + (i * 128 + tid) * 16);
                const uint32_t ww[4] = {w.x, w.y, w.z, w.w};
#pragma unroll
                for (int j = 0; j < 4; j++) {
                    e[i * 8 + 2 * j] = __expf(bf_lo(ww[j]) - m);
                    e[i * 8 + 2 * j + 1] = __expf(bf_hi(ww[j]) - m);
                    sum += e[i * 8 + 2 * j] + e[i * 8 + 2 * j + 1];
                }
            }
#pragma unroll
            for (int o = 16; o; o >>= 1) sum += __shfl_xor_sync(0xffffffffu, sum, o);
            if (lane == 0) sts32f(sb + SM_STAT + 16 + warp * 4, sum);
            bar_sync(1, 128);
            const uint4 sm = lds128(sb + SM_STAT + 16);
            const float inv = 1.f / ((__uint_as_float(sm.x) + __uint_as_float(sm.y)) +
                                     (__uint_as_float(sm.z) + __uint_as_float(sm.w)));
#pragma unroll
            for (int i = 0; i < 4; i++) {
                uint4 w;
                w.x = pack_bf(e[i * 8 + 0] * inv, e[i * 8 + 1] * inv);
                w.y = pack_bf(e[i * 8 + 2] * inv, e[i * 8 + 3] * inv);
                w.z = pack_bf(e[i * 8 + 4] * inv, e[i * 8 + 5] * inv);
                w.w = pack_bf(e[i * 8 + 6] * inv, e[i * 8 + 7] * inv);
                sts128(sb + SM_P + (i * 128 + tid) * 16, w);
            }
            bar_sync(1, 128);
        }
        {
            uint32_t off[4];
#pragma unroll
            for (int i = 0; i < 4; i++)
                off[i] = sb + SM_RING + ((mi >> 1) * 8 + r) * 512 + warp * 128 + (((2 * i + (mi & 1)) ^ r) << 4);
            const uint32_t pmask = t == (g >> 1) ? ((g & 1) ? 0xffff0000u : 0x0000ffffu) : 0u;
            uint32_t* odst = gx->o + ((c & 15) * 8 + (c >> 4)) * 128 + (warp * 2 + (t >> 1)) * 16 + (g >> 1) * 4 +
                             (t & 1) * 2 + (g & 1);
            uint32_t lane2;
            asm volatile("mov.u32 %0, %%laneid;" : "=r"(lane2));
#pragma unroll 1
            for (int pass = 0; pass < 2; pass++) {
                int n = pass * NCH;
                asm volatile("" : "+r"(n));
                float acc[4][4] = {};
                uint32_t psrc = sb + SM_P + t * 32;
                uint32_t va[8][4], vb[8][4] = {};
                uint32_t pt[4] = {};
                uint32_t cur[4];
#pragma unroll
                for (int j = 0; j < 4; j++) cur[j] = off[j] + s * CHUNK;
                uint32_t bar = sb + BAR_FULL + 8 * s, ready = 0;
#pragma unroll 1
                for (int i = n; i > 0; i--) {
                    if (!ready) mbar_wait(bar, ph);
                    const bool wrap = bar == sb + BAR_FULL + 8 * (NS - 1);
                    const uint32_t barn = wrap ? sb + BAR_FULL : bar + 8;
                    ph ^= wrap;
                    const uint4 p0 = lds128(psrc), p1 = lds128(psrc + 16);
#pragma unroll
                    for (int j = 0; j < 2; j++) ldsm4t(va[j], cur[j & 3] + (j >> 2) * 8192);
                    uint32_t tok;
                    asm volatile("{\n.reg .pred p;\nmbarrier.test_wait.parity.shared::cta.b64 p, [%2], %3;\n"
                                 "selp.u32 %0, 1, 0, p;\nselp.u32 %1, %4, %5, p;\n}"
                                 : "=r"(ready), "=r"(tok) : "r"(barn), "r"(ph), "r"(lane), "r"(lane2) : "memory");
#pragma unroll
                    for (int j = 2; j < 8; j++) ldsm4t(va[j], cur[j & 3] + (j >> 2) * 8192);
#pragma unroll
                    for (int j = 0; j < 8; j++) mma(acc[j & 3], vb[j], pt[(j >> 2) * 2], pt[(j >> 2) * 2 + 1]);
#pragma unroll
                    for (int j = 0; j < 8; j++) ldsm4t(vb[j], cur[j & 3] + (2 + (j >> 2)) * 8192);
                    asm volatile("{\n.reg .pred p;\nsetp.eq.u32 p, %1, 0;\n@p mbarrier.arrive.shared::cta.b64 _, [%0];\n}"
                                 ::"r"(bar + 8 * NS), "r"(tok) : "memory");
                    mma(acc[0], va[0], p0.x & pmask, p0.y & pmask);
                    mma(acc[1], va[1], p0.x & pmask, p0.y & pmask);
                    mma(acc[2], va[2], p0.x & pmask, p0.y & pmask);
                    mma(acc[3], va[3], p0.x & pmask, p0.y & pmask);
                    mma(acc[0], va[4], p0.z & pmask, p0.w & pmask);
                    mma(acc[1], va[5], p0.z & pmask, p0.w & pmask);
                    mma(acc[2], va[6], p0.z & pmask, p0.w & pmask);
                    mma(acc[3], va[7], p0.z & pmask, p0.w & pmask);
                    pt[0] = p1.x & pmask;
                    pt[1] = p1.y & pmask;
                    pt[2] = p1.z & pmask;
                    pt[3] = p1.w & pmask;
                    psrc += 128;
                    bar = barn;
                    const uint32_t step = wrap ? -(NS - 1) * CHUNK : CHUNK;
#pragma unroll
                    for (int j = 0; j < 4; j++) cur[j] += step;
                }
#pragma unroll
                for (int j = 0; j < 8; j++) mma(acc[j & 3], vb[j], pt[(j >> 2) * 2], pt[(j >> 2) * 2 + 1]);
                float ev[4], od[4];
#pragma unroll
                for (int T = 0; T < 4; T++) {
                    ev[T] = acc[T][0] + acc[T][3];
                    od[T] = acc[T][1] + acc[T][2];
                }
                ev[0] += __shfl_xor_sync(0xffffffffu, ev[1], 1);
                od[0] += __shfl_xor_sync(0xffffffffu, od[1], 1);
                ev[2] += __shfl_xor_sync(0xffffffffu, ev[3], 1);
                od[2] += __shfl_xor_sync(0xffffffffu, od[3], 1);
                ev[0] += __shfl_xor_sync(0xffffffffu, ev[2], 2);
                od[0] += __shfl_xor_sync(0xffffffffu, od[2], 2);
                const float other = __shfl_xor_sync(0xffffffffu, (g & 1) ? ev[0] : od[0], 4);
                const uint32_t w = (g & 1) ? pack_bf(other, od[0]) : pack_bf(ev[0], other);
                xst32(odst, n ? w : EMPTY);
                __syncwarp();
                if (!n && lane == 0) mbar_arrive(sb + BAR_DRY);
                if (c < 112) {
                    bar_sync(1, 128);
                    if (tid == 0) {
                        const uint32_t on = n ? 0xffffffffu : 0u;
                        mbar_wait(sb + BAR_W0, ~on & 1);
                        l2_prefetch(p.w1 + c * 7168, 14336, on);
                        spin((is_f1 ? W1_DELAY : PF_DELAY) & on);
                        if (!is_f1) {
                            l2_prefetch(p.w2 + fi * 14336, 28672, on);
                            mbar_wait(sb + BAR_E1, ~on & 1);
                            spin(W2_DELAY & on);
                        }
                        tile_loads(sb + (n ? SM_WX : SM_WO + 8192), is_f1 ? &p.map_w1 : &p.map_w2,
                                   is_f1 ? fi * 32 : (fi % 28) * 16, n ? 0 : 1 << 20, is_f1 ? 64 : 224, is_f1 ? 4096 : 7168,
                                   sb + (n ? BAR_W1 : BAR_X), n ? 8 - is_f1 : 1);
                    }
                }
            }
        }
    } else {
        const int ew = warp - 5, et = tid - 160;
        const int r = lane & 7, mi = lane >> 3;
        {
            uint32_t w[7];
#pragma unroll
            for (int i = 0; i < 7; i++)
                asm volatile("ld.global.nc.u32 %0, [%1];" : "=r"(w[i]) : "l"((const uint32_t*)xin + ew * 224 + i * 32 + lane));
            bar_sync(0, NTHREADS);
            layernorm_row(w, sb + SM_XN + ew * 912, lane);
            mbar_wait(sb + BAR_WQ, 0);
            uint32_t a[8][4];
            frags_w448(a, sb + SM_WQ, ew, lane);
            const float2 q = gemv448(a, sb, ew, lane, et);
            if (et < 128) xst32(gx->q + ((et >> 4) * 16 + (c >> 3)) * 128 + (c & 7) * 16 + (et & 15), ~pack_bf(q.x, q.y));
            if (et == 255) mbar_arrive(sb + BAR_QP);
        }
        const int hh = c / 7, jj = c - hh * 7;
        const int cg = fi % 28, half = fi / 28;
        const int ht0 = (c - 112) * 7 + min(ew, 6);
        uint32_t side;
        asm volatile("ld.global.nc.u32 %0, [%1];" : "=r"(side)
                     : "l"(c < 112 ? (is_f1 ? p.b1 + fi * 32 + (et & 15) * 2 : p.b2 + cg * 16 + r * 2)
                           : xin + ((ht0 & 6) + (mi & 1)) * DM + (ht0 >> 3) * 32 + (r & 3) * 8 + (ht0 & 1) * 4 + (r >> 2) * 2));
        uint32_t seen_prog = 0;
#pragma unroll 1
        for (int pass = 0; pass < 2; pass++) {
            uint32_t live = pass;
            asm volatile("" : "+r"(live));
            const uint32_t want = 0u - live, wipe = ~want;
            const int et = pin(tid - 160), ew = et >> 5, lane = et & 31;
            const int g = lane >> 2, t = lane & 3, r = lane & 7, mi = lane >> 3;
            if (et == 0) {
                if (!live) {
                    mbar_wait(sb + BAR_Q, 0);
                } else if (c < 112) {
                    mbar_wait(sb + BAR_X, 0);
                    mbar_wait(sb + BAR_X + 8, 0);
                }
#pragma unroll 1
                for (int it = 0; it < SPIN_LIMIT; it++) {
                    const uint32_t prog = ctl_load(sb + SM_PROG);
                    int total = 0;
                    if (prog == seen_prog) __nanosleep(100);
                    if (prog != seen_prog || prog >= 2 * NCH - 8)
                        asm volatile("ld.relaxed.gpu.global.u32 %0, [%1];" : "=r"(total) : "l"(gx->count + 32) : "memory");
                    if (total >= ALL_CHUNKS - LIFT_LEFT) {
                        ctl_store(sb + SM_DEPTH, NS);
                    } else if (prog != seen_prog) {
                        const int lead = prog * NCTA - total;
                        ctl_store(sb + SM_DEPTH, lead >= LEAD1 ? 1 : lead >= LEAD2 ? 2 : lead >= LEAD2 - 128 ? 3 : lead >= LEAD2 - 256 ? 4 : NS);
                    }
                    seen_prog = prog;
                    if (live ? total >= ALL_CHUNKS - (c < 112 ? TRIG_LEFT : 0) : mbar_test(sb + BAR_DRY, 0)) break;
                }
                tile_loads(sb + SM_WO, &p.map_wo, jj * 64, live ? hh * 256 : 1 << 20, 64, 8192, sb + (live ? BAR_WO : BAR_X + 8),
                           c >= 112 ? 0 : live ? 4 : 1);
            } else if (et == 32 && live) {
                uint32_t seen;
                mbar_wait(sb + BAR_DRY, 0);
                asm volatile("atom.release.gpu.global.add.u32 %0, [%1], 1;" : "=r"(seen) : "l"(gx->count) : "memory");
                int it = 0;
                for (seen++; seen < NCTA && ++it < SPIN_LIMIT;) {
                    __nanosleep(512);
                    asm volatile("ld.relaxed.gpu.global.u32 %0, [%1];" : "=r"(seen) : "l"(gx->count) : "memory");
                }
                asm volatile("ld.acquire.gpu.global.u32 %0, [%1];" : "=r"(seen) : "l"(gx->count) : "memory");
            }
            __syncwarp();
            bar_sync(2, 256);
            if (c >= 112) {
                if (ew < 7) {
                    const bool odd = mi & 1;
                    const int ht = (c - 112) * 7 + ew;
                    float a0, a1;
                    uint32_t* const dst = gx->h + pin((((mi >> 1) * 14 + (ht >> 3)) * 8 + (ht & 6) + (mi & 1)) * 16 + (ht & 1) * 8 + r);
                    Poll<4, 128> in(gx->part + pin(ht * 512 + lane * 4), want, want);
                    spin(R_DELAY & want);
                    in.finish([&] {
                        const uint4 (&v)[4] = in.v;
                        const float f0 = (__uint_as_float(v[0].x) + __uint_as_float(v[1].x)) + (__uint_as_float(v[2].x) + __uint_as_float(v[3].x));
                        const float f1 = (__uint_as_float(v[0].y) + __uint_as_float(v[1].y)) + (__uint_as_float(v[2].y) + __uint_as_float(v[3].y));
                        const float f2 = (__uint_as_float(v[0].z) + __uint_as_float(v[1].z)) + (__uint_as_float(v[2].z) + __uint_as_float(v[3].z));
                        const float f3 = (__uint_as_float(v[0].w) + __uint_as_float(v[1].w)) + (__uint_as_float(v[2].w) + __uint_as_float(v[3].w));
                        a0 = (odd ? f1 : f0) + __shfl_xor_sync(0xffffffffu, odd ? f0 : f1, 8);
                        a1 = (odd ? f3 : f2) + __shfl_xor_sync(0xffffffffu, odd ? f2 : f3, 8);
                    });
                    a0 += __shfl_xor_sync(0xffffffffu, a0, 16);
                    a1 += __shfl_xor_sync(0xffffffffu, a1, 16);
                    xst32(dst, bf2_add(side, pack_bf(a0, a1)) | wipe);
                }
                if (!live) bar_sync(3, 256);
                continue;
            }
            {
                const uint32_t fa = pin(sb + SM_WO + ((ew >> 1) * 64 + (mi >> 1) * 8 + r) * 128 + ((((ew & 1) * 4 + (mi & 1)) ^ r) << 4));
                const uint32_t wb = pin(sb + SM_RED + ((ew >> 1) * 544 + t * 136 + (ew & 1) * 64 + g * 2) * 4);
                const uint32_t rb = pin(sb + SM_RED + ((ew & 3) * 136 + ((ew >> 2) * 32 + (r >> 1) * 8 + mi * 2 + (r & 1)) * 2) * 4);
                uint32_t* const pdst = gx->part + pin((((jj * 8 + ew) * 2 + (lane >> 4)) * 16 + hh) * 32 + (lane & 15) * 2);
                Poll<2, 16> in(gx->o + pin((hh * 8 + g) * 128 + (ew >> 1) * 32 + t * 4), want, want);
                spin_or(O_DELAY & want, sb + BAR_WO + 8 * (ew >> 1));
                in.until(sb + BAR_WO + 8 * (ew >> 1));
                uint32_t a[8][4];
#pragma unroll
                for (int i = 0; i < 4; i++) {
                    const int ks = (i >> 1) + (i & 1) * 2;
                    ldsm4t(a[ks * 2], fa + ks * 2048);
                    ldsm4t(a[ks * 2 + 1], (fa ^ 32) + ks * 2048);
                }
                float acc[2][2][4];
                in.finish([&] {
#pragma unroll
                    for (int i = 0; i < 2; i++) {
                        mma0(acc[i][0], a[i * 4], in.v[i].x, in.v[i].y);
                        mma0(acc[i][1], a[i * 4 + 1], in.v[i].x, in.v[i].y);
                    }
#pragma unroll
                    for (int mt = 0; mt < 2; mt++) {
                        mma(acc[0][mt], a[2 + mt], in.v[0].z, in.v[0].w);
                        mma(acc[1][mt], a[6 + mt], in.v[1].z, in.v[1].w);
                    }
                });
#pragma unroll
                for (int mt = 0; mt < 2; mt++) {
                    sts64f(wb + mt * 128, acc[0][mt][0] + acc[1][mt][0], acc[0][mt][1] + acc[1][mt][1]);
                    sts64f(wb + mt * 128 + 64, acc[0][mt][2] + acc[1][mt][2], acc[0][mt][3] + acc[1][mt][3]);
                }
                bar_sync(2, 256);
                float2 v[4];
#pragma unroll
                for (int w = 0; w < 4; w++) v[w] = lds64f(rb + w * 2176);
                const float s0 = (v[0].x + v[1].x) + (v[2].x + v[3].x);
                const float s1 = (v[0].y + v[1].y) + (v[2].y + v[3].y);
                xst64(pdst, __float_as_uint(s0) | wipe, __float_as_uint(s1) | wipe);
            }
            if (et == 0 && live) mbar_arrive(sb + BAR_E1);
            const uint32_t wbar = sb + BAR_W1 + 8 * ew;
            if (is_f1) {
                constexpr uint32_t ONES = 0x3f803f80u;
                if (ew < 7) {
                    const int b = (et >> 4) & 7, pr = et & 15;
                    const uint32_t fa = pin(sb + SM_WX + (ew * 64 + (mi >> 1) * 8 + r) * 64 + (((mi & 1) ^ (r >> 1)) << 4));
                    const uint32_t wb = pin(sb + SM_RED + (ew * 288 + t * 72 + g) * 4);
                    const uint32_t sw = pin(sb + SM_RED + (ew * 288 + g * 36 + (t == (g >> 1) ? 32 : 34)) * 4);
                    const uint32_t rs = pin(sb + SM_RED + b * 144 + 128), rz = pin(sb + SM_RED + b * 144 + pr * 8);
                    const uint32_t cw = pin(sb + SM_XN + (ew * 32 + g + (t >> 1) * 16 + (t & 1) * 8) * 4), cr = pin(sb + SM_XN + pr * 8);
                    const bool odd = pin(g & 1);
                    uint32_t* const dst = gx->r + pin((((b >> 2) * 56 + fi) * 4 + (b & 3)) * 16 + (pr & 3) * 4 + (pr >> 2));
                    Poll<2, 128> in(gx->h + pin(((fi & 1) * 14 + ew * 2) * 128 + lane * 4), want, want);
                    mbar_wait(wbar, wipe & 1);
                    uint32_t a[8][4];
#pragma unroll
                    for (int ks = 0; ks < 4; ks++) {
                        ldsm4t(a[ks * 2], fa + ks * 1024);
                        ldsm4t(a[ks * 2 + 1], (fa ^ 32) + ks * 1024);
                    }
                    float cs[2][4] = {}, z[2][2][4], st[2][4];
#pragma unroll
                    for (int ks = 0; ks < 4; ks++) {
                        mma(cs[0], a[ks * 2], ONES, ONES);
                        mma(cs[1], a[ks * 2 + 1], ONES, ONES);
                    }
                    sts32f(cw, (t & 1) ? ((t & 2) ? cs[1][2] : cs[0][2]) : ((t & 2) ? cs[1][0] : cs[0][0]));
                    bar_sync(4, 224);
                    float2 cv[7];
#pragma unroll
                    for (int w = 0; w < 7; w++) cv[w] = lds64f(cr + w * 128);
                    const float cs0 = ((cv[0].x + cv[1].x) + (cv[2].x + cv[3].x)) + ((cv[4].x + cv[5].x) + cv[6].x);
                    const float cs1 = ((cv[0].y + cv[1].y) + (cv[2].y + cv[3].y)) + ((cv[4].y + cv[5].y) + cv[6].y);
                    in.finish([&] {
#pragma unroll
                        for (int i = 0; i < 2; i++) {
                            const uint32_t sa[4] = {in.v[i].x, ONES, in.v[i].y, ONES};
                            mma0(z[i][0], a[i * 4], in.v[i].x, in.v[i].y);
                            mma0(z[i][1], a[i * 4 + 1], in.v[i].x, in.v[i].y);
                            mma0(st[i], sa, in.v[i].x, in.v[i].y);
                        }
                    });
#pragma unroll
                    for (int i = 0; i < 2; i++) mma(z[i][0], a[i * 4 + 2], in.v[i].z, in.v[i].w);
#pragma unroll
                    for (int i = 0; i < 2; i++) mma(z[i][1], a[i * 4 + 3], in.v[i].z, in.v[i].w);
#pragma unroll
                    for (int i = 0; i < 2; i++) {
                        const uint32_t sa[4] = {in.v[i].z, ONES, in.v[i].w, ONES};
                        mma(st[i], sa, in.v[i].z, in.v[i].w);
                    }
#pragma unroll
                    for (int mt = 0; mt < 2; mt++) {
                        sts32f(wb + mt * 64, z[0][mt][0] + z[1][mt][0]);
                        sts32f(wb + mt * 64 + 144, z[0][mt][1] + z[1][mt][1]);
                        sts32f(wb + mt * 64 + 32, z[0][mt][2] + z[1][mt][2]);
                        sts32f(wb + mt * 64 + 176, z[0][mt][3] + z[1][mt][3]);
                    }
                    sts64f(sw, odd ? st[0][3] + st[1][3] : st[0][2] + st[1][2], odd ? st[0][1] + st[1][1] : st[0][0] + st[1][0]);
                    bar_sync(4, 224);
                    if (ew < 4) {
                        float2 sv[7], zv[7];
#pragma unroll
                        for (int w = 0; w < 7; w++) sv[w] = lds64f(rs + w * 1152);
#pragma unroll
                        for (int w = 0; w < 7; w++) zv[w] = lds64f(rz + w * 1152);
                        const float mu = (((sv[0].x + sv[1].x) + (sv[2].x + sv[3].x)) + ((sv[4].x + sv[5].x) + sv[6].x)) * (1.f / DM);
                        const float sq = ((sv[0].y + sv[1].y) + (sv[2].y + sv[3].y)) + ((sv[4].y + sv[5].y) + sv[6].y);
                        const float inv = inv_std(bf_round(fmaxf(fmaf(sq, 1.f / DM, -mu * mu), 0.f)));
                        const float mean = bf_round(mu);
                        const float z0 = ((zv[0].x + zv[1].x) + (zv[2].x + zv[3].x)) + ((zv[4].x + zv[5].x) + zv[6].x);
                        const float z1 = ((zv[0].y + zv[1].y) + (zv[2].y + zv[3].y)) + ((zv[4].y + zv[5].y) + zv[6].y);
                        const uint32_t u = pack_bf(fmaf(-mean, cs0, z0) * inv, fmaf(-mean, cs1, z1) * inv);
                        xst32(dst, bf2_relu_sq(bf2_add(u, side)) | wipe);
                    }
                    if (c == 0 && et == 128 && live) {
                        xst32(gx->count, 0);
                        xst32(gx->count + 32, 0);
                    }
                }
            } else {
                const uint32_t fa = pin(sb + SM_WX + (ew * 224 + (mi >> 1) * 8 + r) * 32 + (((mi & 1) ^ (r >> 2)) << 4));
                const uint32_t wb = pin(sb + SM_XN + (ew * 160 + (t & 1) * 80 + (g >> 1) * 4 + (t >> 1) * 2 + (g & 1)) * 4);
                const uint32_t rb = pin(sb + SM_XN + (mi * 40 + r * 4) * 4);
                const bool upper = pin(t >> 1), first = pin(ew == 0);
                uint32_t* const dst = (live ? (uint32_t*)p.out : gx->sink) + pin((half * 4 + mi) * 224 + cg * 8 + r);
                Poll<4, 128, true> in(gx->r + pin((half * 56 + ew * 7) * 64 + lane * 4), want, lane < 16 ? want : 0u,
                                      gx->h + pin((((fi & 1) * 14 + (cg >> 1)) * 8 + half * 4 + mi) * 16 + (r & 3) * 4 +
                                                  (cg & 1) * 2 + (r >> 2)),
                                      ew == 0 ? want : 0u);
                mbar_wait(wbar, wipe & 1);
                uint32_t a[14][4];
#pragma unroll
                for (int ks = 0; ks < 14; ks++) ldsm4t(a[ks], fa + ks * 512);
                float acc[4][4];
                const auto step = [&](int i) {
                    mma(acc[0], a[4 * i], in.v[i].x, in.v[i].y);
                    mma(acc[1], a[4 * i + 1], in.v[i].z, in.v[i].w);
                    if (i < 3) {
                        mma(acc[2], a[4 * i + 2], in.v[i].x, in.v[i].y);
                        mma(acc[3], a[4 * i + 3], in.v[i].z, in.v[i].w);
                    }
                };
                in.finish([&] {
                    mma0(acc[0], a[0], in.v[0].x, in.v[0].y);
                    mma0(acc[1], a[1], in.v[0].z, in.v[0].w);
                    mma0(acc[2], a[2], in.v[0].x, in.v[0].y);
                    mma0(acc[3], a[3], in.v[0].z, in.v[0].w);
                    step(1);
                });
                step(2);
                step(3);
                sts32f(wb, upper ? acc[2][0] + acc[3][0] : acc[0][0] + acc[1][0]);
                sts32f(wb + 160, upper ? acc[2][1] + acc[3][1] : acc[0][1] + acc[1][1]);
                sts32f(wb + 64, upper ? acc[2][2] + acc[3][2] : acc[0][2] + acc[1][2]);
                sts32f(wb + 224, upper ? acc[2][3] + acc[3][3] : acc[0][3] + acc[1][3]);
                bar_sync(2, 256);
                if (first) {
                    float x[8], y[8];
#pragma unroll
                    for (int w = 0; w < 8; w++) {
                        const uint4 q = lds128(rb + w * 640);
                        x[w] = __uint_as_float(q.x) + __uint_as_float(q.z);
                        y[w] = __uint_as_float(q.y) + __uint_as_float(q.w);
                    }
                    const float s0 = ((x[0] + x[1]) + (x[2] + x[3])) + ((x[4] + x[5]) + (x[6] + x[7]));
                    const float s1 = ((y[0] + y[1]) + (y[2] + y[3])) + ((y[4] + y[5]) + (y[6] + y[7]));
                    *dst = bf2_add(in.word, bf2_add(pack_bf(s0, s1), side));
                }
                exit_if(live);
            }
            if (!live) bar_sync(3, 256);
        }
    }
}

using EncodeFn = CUresult (*)(CUtensorMap*, CUtensorMapDataType, cuuint32_t, void*, const cuuint64_t*, const cuuint64_t*,
                              const cuuint32_t*, const cuuint32_t*, CUtensorMapInterleave, CUtensorMapSwizzle,
                              CUtensorMapL2promotion, CUtensorMapFloatOOBfill);

void encode_map(EncodeFn fn, CUtensorMap* map, const void* base, int rows, int cols, int box_rows, int box_cols,
                CUtensorMapSwizzle swizzle) {
    const cuuint64_t dims[2] = {(cuuint64_t)cols, (cuuint64_t)rows};
    const cuuint64_t strides[1] = {(cuuint64_t)cols * 2};
    const cuuint32_t box[2] = {(cuuint32_t)box_cols, (cuuint32_t)box_rows};
    const cuuint32_t steps[2] = {1, 1};
    fn(map, CU_TENSOR_MAP_DATA_TYPE_BFLOAT16, 2, const_cast<void*>(base), dims, strides, box, steps,
       CU_TENSOR_MAP_INTERLEAVE_NONE, swizzle, CU_TENSOR_MAP_L2_PROMOTION_L2_128B, CU_TENSOR_MAP_FLOAT_OOB_FILL_NONE);
}

}

extern "C" void kernel_launch(void* const* d_in, const int* in_sizes, int n_in, void* d_out, int out_size) {
    (void)in_sizes; (void)n_in; (void)out_size;
    Params p;
    p.w1 = (const __nv_bfloat16*)d_in[6];
    p.b1 = (const __nv_bfloat16*)d_in[7];
    p.w2 = (const __nv_bfloat16*)d_in[8];
    p.b2 = (const __nv_bfloat16*)d_in[9];
    p.out = (__nv_bfloat16*)d_out;
    Exchange* xch = nullptr;
    cudaGetSymbolAddress((void**)&xch, g_x);
    void* fn = nullptr;
    cudaDriverEntryPointQueryResult found;
    cudaGetDriverEntryPoint("cuTensorMapEncodeTiled", &fn, cudaEnableDefault, &found);
    encode_map((EncodeFn)fn, &p.map_wo, d_in[4], NH * DH, DM, 64, 64, CU_TENSOR_MAP_SWIZZLE_128B);
    encode_map((EncodeFn)fn, &p.map_w1, p.w1, DM, FF, 64, 32, CU_TENSOR_MAP_SWIZZLE_64B);
    encode_map((EncodeFn)fn, &p.map_w2, p.w2, FF, DM, 224, 16, CU_TENSOR_MAP_SWIZZLE_32B);
    cudaFuncSetAttribute(fused_decode_kernel, cudaFuncAttributeMaxDynamicSharedMemorySize, SM_TOTAL);
    fused_decode_kernel<<<NCTA, NTHREADS, SM_TOTAL>>>((const __nv_bfloat16*)d_in[3], (const __nv_bfloat16*)d_in[0],
                                                      (const char*)d_in[1], (const char*)d_in[2], xch, p);
}
```
